```python
import torch

def _softmax(x, axis=-1):
    return torch.softmax(x, dim=axis)

def _gelu(x):
    return torch.nn.functional.gelu(x, approximate='tanh')

def _silu(x):
    return torch.nn.functional.silu(x)

def _sigmoid(x):
    return torch.sigmoid(x)

def _layernorm(x, axis=-1, eps=1e-05):
    m = x.mean(dim=axis, keepdim=True)
    v = x.var(dim=axis, keepdim=True, unbiased=False)
    return (x - m) / torch.sqrt(v + eps)

def _scatter_add(tgt, idx, src, axis=0):
    return tgt.clone().index_add_(axis, idx, src)

def _segment_sum(src, seg, n):
    out = torch.zeros((n,) + src.shape[1:], dtype=src.dtype)
    return out.index_add_(0, seg, src)

def _pad(x, pw):
    flat = tuple((v for pair in reversed(pw) for v in pair))
    return torch.nn.functional.pad(x, flat)
kernel_name = 'standalone__kv_cache_quant_pre_rope_vs_post_rope__decode'

def setup_inputs():

    _w = lambda a: (lambda t: t.to(torch.bfloat16) if t.is_floating_point() else t)(torch.as_tensor(a))
    B, Sq, Skv = (1, 1, 8192)
    H, Dh0 = (32, 128)
    G = 64 if 64 > 0 else Dh0
    G = max(2, G // 2 * 2)
    Dh = max(G, Dh0 // G * G)
    Skv = max(Skv, Sq)
    ng = Dh // G
    bits = 4 if 4 > 1 else 4
    bits = max(2, min(8, bits))
    qmax = (1 << bits) - 1
    half = Dh // 2
    inv = 1.0 / 10000.0 ** (torch.arange(half) / max(1, half))
    ang_k = torch.arange(Skv)[:, None] * inv[None, :]
    ang_q = torch.arange(Skv - Sq, Skv)[:, None] * inv[None, :]
    kc = torch.cat([torch.cos(ang_k), torch.cos(ang_k)], dim=-1)
    ks = torch.cat([torch.sin(ang_k), torch.sin(ang_k)], dim=-1)
    qc = torch.cat([torch.cos(ang_q), torch.cos(ang_q)], dim=-1)
    qs = torch.cat([torch.sin(ang_q), torch.sin(ang_q)], dim=-1)
    qk_i = torch.randint(0, qmax + 1, (B, H, Skv, Dh)).to(torch.int32)
    qv_i = torch.randint(0, qmax + 1, (B, H, Skv, Dh)).to(torch.int32)
    ksc = torch.abs((lambda *s: torch.randn(*s, dtype=torch.bfloat16) * 0.2)(B, H, Skv, ng)) * 0.1 + 0.01
    kzp = torch.full((B, H, Skv, ng), qmax / 2.0)
    vsc = torch.abs((lambda *s: torch.randn(*s, dtype=torch.bfloat16) * 0.2)(B, H, Skv, ng)) * 0.1 + 0.01
    vzp = torch.full((B, H, Skv, ng), qmax / 2.0)
    return {'q': _w((lambda *s: torch.randn(*s, dtype=torch.bfloat16) * 6.4)(B, H, Sq, Dh) * 0.5), 'qk': _w(qk_i), 'k_scales': _w(ksc), 'k_zeros': _w(kzp), 'qv': _w(qv_i), 'v_scales': _w(vsc), 'v_zeros': _w(vzp), 'q_cos': _w(qc), 'q_sin': _w(qs), 'k_cos': _w(kc), 'k_sin': _w(ks)}

def reference(q, qk, k_scales, k_zeros, qv, v_scales, v_zeros, q_cos, q_sin, k_cos, k_sin):
    B, H, Sq, Dh = q.shape
    ng = k_scales.shape[-1]
    G = Dh // ng
    half = Dh // 2
    ks = (lambda x, n, axis: torch.repeat_interleave(x, n, dim=axis))(k_scales, G, axis=-1)
    kz = (lambda x, n, axis: torch.repeat_interleave(x, n, dim=axis))(k_zeros, G, axis=-1)
    k = ((lambda x, dt: x.to(dt))(qk, q.dtype) - kz) * ks
    vs = (lambda x, n, axis: torch.repeat_interleave(x, n, dim=axis))(v_scales, G, axis=-1)
    vz = (lambda x, n, axis: torch.repeat_interleave(x, n, dim=axis))(v_zeros, G, axis=-1)
    v = ((lambda x, dt: x.to(dt))(qv, q.dtype) - vz) * vs
    k1 = k[..., :half].clone()
    k2 = k[..., half:].clone()
    krh = torch.concatenate([-k2, k1], axis=-1)
    kr = k * k_cos[None, None, :, :] + krh * k_sin[None, None, :, :]
    q1 = q[..., :half].clone()
    q2 = q[..., half:].clone()
    qrh = torch.concatenate([-q2, q1], axis=-1)
    qr = q * q_cos[None, None, :, :] + qrh * q_sin[None, None, :, :]
    logits = torch.einsum('bhqd,bhkd->bhqk', qr, kr) * float(Dh) ** (-0.5)
    attn = _softmax(logits, axis=-1)
    out = torch.einsum('bhqk,bhkd->bhqd', attn, v)
    return out
```

```cpp
#include <cuda_runtime.h>
#include <cuda_bf16.h>
#include <stdint.h>

#define KU 4
#define VU 8
#define MINB 4
#define ORDER 0
#define LAG 2
#define EVF 0

namespace {

constexpr int H = 32, S = 8192, D = 128;
constexpr int NW = 8;
constexpr int HG = 8;
constexpr int NG = H / HG;
constexpr int KC_PER_G = S / KU;
constexpr int NK = KC_PER_G * NG;
constexpr int VROWS = NW * VU;
constexpr int VC = S / VROWS;
constexpr int RS = 4;
constexpr int VSEG = VC + RS;
constexpr int NV = H * VSEG + LAG * RS;
constexpr int GRID = NK + NV;
constexpr int SPIN_LIMIT = 1 << 22;

__device__ float g_logits[H * S];
__device__ float4 g_part[H * VC * (D / 4)];
__device__ float2 g_ml[H * VC];
__device__ unsigned g_cnt;

__device__ __forceinline__ int4 ld_stream(const int4* p, uint64_t pol) {
    int4 v;
    asm volatile("ld.global.nc.L1::no_allocate.v4.s32 {%0,%1,%2,%3}, [%4];"
                 : "=r"(v.x), "=r"(v.y), "=r"(v.z), "=r"(v.w) : "l"(p));
    return v;
}
__device__ __forceinline__ uint2 ld_nc8(const void* p) {
    uint2 v;
    asm volatile("ld.global.nc.v2.u32 {%0,%1}, [%2];" : "=r"(v.x), "=r"(v.y) : "l"(p));
    return v;
}
__device__ __forceinline__ uint4 ld_nc16_na(const void* p) {
    uint4 v;
    asm volatile("ld.global.nc.L1::no_allocate.v4.u32 {%0,%1,%2,%3}, [%4];"
                 : "=r"(v.x), "=r"(v.y), "=r"(v.z), "=r"(v.w) : "l"(p));
    return v;
}
__device__ __forceinline__ uint32_t ld_nc2_na(const void* p) {
    uint16_t v;
    asm volatile("ld.global.nc.L1::no_allocate.u16 %0, [%1];" : "=h"(v) : "l"(p));
    return (uint32_t)v;
}
__device__ __forceinline__ uint32_t ld_rlx4(const void* p) {
    uint32_t v;
    asm volatile("ld.relaxed.gpu.global.u32 %0, [%1];" : "=r"(v) : "l"(p) : "memory");
    return v;
}
__device__ __forceinline__ uint2 ld_rlx8(const void* p) {
    uint2 v;
    asm volatile("ld.relaxed.gpu.global.v2.u32 {%0,%1}, [%2];" : "=r"(v.x), "=r"(v.y) : "l"(p) : "memory");
    return v;
}
__device__ __forceinline__ uint4 ld_rlx16(const void* p) {
    uint4 v;
    asm volatile("ld.relaxed.gpu.global.v4.u32 {%0,%1,%2,%3}, [%4];"
                 : "=r"(v.x), "=r"(v.y), "=r"(v.z), "=r"(v.w) : "l"(p) : "memory");
    return v;
}
__device__ __forceinline__ void st_rlx4(void* p, uint32_t v) {
    asm volatile("st.relaxed.gpu.global.u32 [%0], %1;" :: "l"(p), "r"(v) : "memory");
}
__device__ __forceinline__ void st_rlx8(void* p, uint32_t a, uint32_t b) {
    asm volatile("st.relaxed.gpu.global.v2.u32 [%0], {%1,%2};" :: "l"(p), "r"(a), "r"(b) : "memory");
}
__device__ __forceinline__ uint32_t tagf(float x, uint32_t tag) { return (__float_as_uint(x) & ~3u) | tag; }
__device__ __forceinline__ float bf_lo(uint32_t x) { return __uint_as_float(x << 16); }
__device__ __forceinline__ float bf_hi(uint32_t x) { return __uint_as_float(x & 0xffff0000u); }
__device__ __forceinline__ float ex2(float x) { float y; asm("ex2.approx.ftz.f32 %0, %1;" : "=f"(y) : "f"(x)); return y; }
__device__ __forceinline__ uint32_t bf2_mul(uint32_t a, uint32_t b) {
    uint32_t r; asm("mul.rn.bf16x2 %0, %1, %2;" : "=r"(r) : "r"(a), "r"(b)); return r;
}
__device__ __forceinline__ uint32_t bf2_add(uint32_t a, uint32_t b) {
    uint32_t r; asm("add.rn.bf16x2 %0, %1, %2;" : "=r"(r) : "r"(a), "r"(b)); return r;
}

struct Params {
    const __nv_bfloat16* q;
    const int4* qk;
    const __nv_bfloat16* ks;
    const __nv_bfloat16* kz;
    const int4* qv;
    const __nv_bfloat16* vs;
    const __nv_bfloat16* vz;
    const __nv_bfloat16* qcos;
    const __nv_bfloat16* qsin;
    const __nv_bfloat16* kcos;
    const __nv_bfloat16* ksin;
    __nv_bfloat16* out;
};

__device__ __forceinline__ uint32_t read_tag() {
    uint32_t c;
    asm volatile("ld.global.ca.u32 %0, [%1];" : "=r"(c) : "l"(&g_cnt));
    return ((c / (H * RS)) + 1u) & 3u;
}

__device__ __forceinline__ void k_role(const Params& P, int g, int rb, uint64_t pol) {
    const int w = threadIdx.x >> 5, lane = threadIdx.x & 31;
    const int h = g * HG + w;
    const int r0 = rb * KU;
    const size_t row = (size_t)h * S + r0;
    int4 kv[KU];
#pragma unroll
    for (int u = 0; u < KU; u++) kv[u] = ld_stream(P.qk + (row + u) * 32 + lane, pol);
    uint2 cs[KU], sn[KU];
#pragma unroll
    for (int u = 0; u < KU; u++) {
        cs[u] = ld_nc8(P.kcos + (size_t)(r0 + u) * D + lane * 4);
        sn[u] = ld_nc8(P.ksin + (size_t)(r0 + u) * D + (lane ^ 16) * 4);
    }
    uint32_t zz[KU], sc[KU];
#pragma unroll
    for (int u = 0; u < KU; u += 4) {
        uint4 a = ld_nc16_na(P.kz + (row + u) * 2);
        uint4 b = ld_nc16_na(P.ks + (row + u) * 2);
        zz[u] = a.x; zz[u + 1] = a.y; zz[u + 2] = a.z; zz[u + 3] = a.w;
        sc[u] = b.x; sc[u + 1] = b.y; sc[u + 2] = b.z; sc[u + 3] = b.w;
    }
    const uint2 qq = ld_nc8(P.q + h * D + lane * 4);
    const uint2 qp = ld_nc8(P.q + h * D + (lane ^ 16) * 4);
    const uint2 qc = ld_nc8(P.qcos + lane * 4);
    const uint2 qs = ld_nc8(P.qsin + lane * 4);
    const uint32_t tag = read_tag();
    const uint32_t neg = (lane < 16) ? 0x80008000u : 0u;
    uint2 qr;
    qr.x = bf2_add(bf2_mul(qq.x, qc.x), bf2_mul(qp.x ^ neg, qs.x));
    qr.y = bf2_add(bf2_mul(qq.y, qc.y), bf2_mul(qp.y ^ neg, qs.y));
    uint2 qo;
    qo.x = __shfl_xor_sync(0xffffffffu, qr.x, 16);
    qo.y = __shfl_xor_sync(0xffffffffu, qr.y, 16);
    const float c = 0.08838834764831845f * 1.4426950408889634f;
    const float cb = (lane < 16) ? c : -c;
    const float qa0 = bf_lo(qr.x) * c, qa1 = bf_hi(qr.x) * c, qa2 = bf_lo(qr.y) * c, qa3 = bf_hi(qr.y) * c;
    const float qb0 = bf_lo(qo.x) * cb, qb1 = bf_hi(qo.x) * cb, qb2 = bf_lo(qo.y) * cb, qb3 = bf_hi(qo.y) * cb;
    const uint32_t sel = (lane < 16) ? 0x1044u : 0x3244u;

    float acc[KU];
#pragma unroll
    for (int u = 0; u < KU; u++) {
        const float z = __uint_as_float(__byte_perm(zz[u], 0u, sel));
        const float s = __uint_as_float(__byte_perm(sc[u], 0u, sel));
        const float a0 = fmaf(qa0, bf_lo(cs[u].x), qb0 * bf_lo(sn[u].x));
        const float a1 = fmaf(qa1, bf_hi(cs[u].x), qb1 * bf_hi(sn[u].x));
        const float a2 = fmaf(qa2, bf_lo(cs[u].y), qb2 * bf_lo(sn[u].y));
        const float a3 = fmaf(qa3, bf_hi(cs[u].y), qb3 * bf_hi(sn[u].y));
        float t = ((float)kv[u].x - z) * a0;
        t = fmaf((float)kv[u].y - z, a1, t);
        t = fmaf((float)kv[u].z - z, a2, t);
        t = fmaf((float)kv[u].w - z, a3, t);
        acc[u] = t * s;
    }
    int idx = 0;
    int off = 16;
#pragma unroll
    for (int n = KU; n > 1; n >>= 1, off >>= 1) {
        const bool up = (lane & off) != 0;
#pragma unroll
        for (int i = 0; i < n / 2; i++) {
            const float keep = up ? acc[i + n / 2] : acc[i];
            const float send = up ? acc[i] : acc[i + n / 2];
            acc[i] = keep + __shfl_xor_sync(0xffffffffu, send, off);
        }
        idx += up ? n / 2 : 0;
    }
#pragma unroll
    for (; off > 0; off >>= 1) acc[0] += __shfl_xor_sync(0xffffffffu, acc[0], off);
    if ((lane & (32 / KU - 1)) == 0) st_rlx4(g_logits + row + idx, tagf(acc[0], tag));
}

__device__ __forceinline__ void v_role(const Params& P, int h, int j, uint64_t pol, float* sm) {
    const int w = threadIdx.x >> 5, lane = threadIdx.x & 31;
    const size_t row = (size_t)h * S + j * VROWS + w * VU;
    int4 vv[VU];
#pragma unroll
    for (int u = 0; u < VU; u++) vv[u] = ld_stream(P.qv + (row + u) * 32 + lane, pol);
    const int i = lane & (2 * VU - 1);
    const uint32_t s16 = ld_nc2_na(P.vs + row * 2 + i);
    const uint32_t z16 = ld_nc2_na(P.vz + row * 2 + i);
    const uint32_t tag = read_tag();
    uint32_t lb = ld_rlx4(g_logits + row + (i >> 1));
    for (int it = 0; (lb & 3u) != tag; it++) {
        if (it > SPIN_LIMIT) __trap();
        lb = ld_rlx4(g_logits + row + (i >> 1));
    }
    __syncwarp();
    const float lg = __uint_as_float(lb);
    float m = lg;
#pragma unroll
    for (int o = 2; o < 2 * VU; o <<= 1) m = fmaxf(m, __shfl_xor_sync(0xffffffffu, m, o));
    float* s_m = sm;
    float* s_l = sm + NW;
    float* s_o = sm + 2 * NW;
    if (lane == 0) s_m[w] = m;
    __syncthreads();
    {
        const float4 a = *(const float4*)(s_m), b = *(const float4*)(s_m + 4);
        m = fmaxf(fmaxf(fmaxf(a.x, a.y), fmaxf(a.z, a.w)), fmaxf(fmaxf(b.x, b.y), fmaxf(b.z, b.w)));
    }
    const float p = ex2(lg - m);
    const float wt = p * __uint_as_float(s16 << 16);
    float corr = wt * __uint_as_float(z16 << 16);
    float l = p;
#pragma unroll
    for (int o = 2; o < 2 * VU; o <<= 1) {
        corr += __shfl_xor_sync(0xffffffffu, corr, o);
        l += __shfl_xor_sync(0xffffffffu, l, o);
    }
    const int gsel = lane >> 4;
    corr = __shfl_sync(0xffffffffu, corr, gsel);
    float wu[VU];
#pragma unroll
    for (int u = 0; u < VU; u++) wu[u] = __shfl_sync(0xffffffffu, wt, 2 * u + gsel);
    float o0 = -corr, o1 = -corr, o2 = -corr, o3 = -corr;
#pragma unroll
    for (int u = 0; u < VU; u++) {
        o0 = fmaf((float)vv[u].x, wu[u], o0);
        o1 = fmaf((float)vv[u].y, wu[u], o1);
        o2 = fmaf((float)vv[u].z, wu[u], o2);
        o3 = fmaf((float)vv[u].w, wu[u], o3);
    }
    *(float4*)(s_o + w * D + lane * 4) = make_float4(o0, o1, o2, o3);
    if (lane == 0) s_l[w] = l;
    __syncthreads();
    const int t = threadIdx.x;
    if (t < D) {
        float r = 0.f;
#pragma unroll
        for (int k = 0; k < NW; k++) r += s_o[k * D + t];
        st_rlx4((float*)(g_part + ((size_t)h * VC + j) * (D / 4)) + t, tagf(r, tag));
    } else if (t == D) {
        float r = 0.f;
#pragma unroll
        for (int k = 0; k < NW; k++) r += s_l[k];
        st_rlx8(g_ml + h * VC + j, tagf(m, tag), tagf(r, tag));
    }
}

__device__ __forceinline__ void r_role(const Params& P, int h, int slice, float* sm) {
    constexpr int NP = VC / 32;
    const int w = threadIdx.x >> 5, lane = threadIdx.x & 31;
    const int c = threadIdx.x & 7, j0 = threadIdx.x >> 3;
    const uint32_t tag = read_tag();
    uint4 pv[NP];
    uint2 ml[NP];
#pragma unroll
    for (int k = 0; k < NP; k++) {
        pv[k] = ld_rlx16(g_part + ((size_t)h * VC + j0 + 32 * k) * (D / 4) + slice * 8 + c);
        ml[k] = ld_rlx8(g_ml + h * VC + j0 + 32 * k);
    }
#pragma unroll
    for (int k = 0; k < NP; k++) {
        for (int it = 0;; it++) {
            const uint32_t bad = ((pv[k].x ^ tag) | (pv[k].y ^ tag) | (pv[k].z ^ tag) | (pv[k].w ^ tag) |
                                  (ml[k].x ^ tag) | (ml[k].y ^ tag)) & 3u;
            if (!bad) break;
            if (it > SPIN_LIMIT) __trap();
            pv[k] = ld_rlx16(g_part + ((size_t)h * VC + j0 + 32 * k) * (D / 4) + slice * 8 + c);
            ml[k] = ld_rlx8(g_ml + h * VC + j0 + 32 * k);
        }
    }
    __syncwarp();
    float m = __uint_as_float(ml[0].x);
#pragma unroll
    for (int k = 1; k < NP; k++) m = fmaxf(m, __uint_as_float(ml[k].x));
    m = fmaxf(m, __shfl_xor_sync(0xffffffffu, m, 8));
    m = fmaxf(m, __shfl_xor_sync(0xffffffffu, m, 16));
    float o0 = 0.f, o1 = 0.f, o2 = 0.f, o3 = 0.f, l = 0.f;
#pragma unroll
    for (int k = 0; k < NP; k++) {
        const float s = ex2(__uint_as_float(ml[k].x) - m);
        o0 = fmaf(s, __uint_as_float(pv[k].x), o0);
        o1 = fmaf(s, __uint_as_float(pv[k].y), o1);
        o2 = fmaf(s, __uint_as_float(pv[k].z), o2);
        o3 = fmaf(s, __uint_as_float(pv[k].w), o3);
        l = fmaf(s, __uint_as_float(ml[k].y), l);
    }
#pragma unroll
    for (int o = 8; o < 32; o <<= 1) {
        o0 += __shfl_xor_sync(0xffffffffu, o0, o);
        o1 += __shfl_xor_sync(0xffffffffu, o1, o);
        o2 += __shfl_xor_sync(0xffffffffu, o2, o);
        o3 += __shfl_xor_sync(0xffffffffu, o3, o);
        l += __shfl_xor_sync(0xffffffffu, l, o);
    }
    float* s_m = sm;
    float* s_l = sm + NW;
    float* s_o = sm + 2 * NW;
    if (lane < 8) *(float4*)(s_o + w * 32 + lane * 4) = make_float4(o0, o1, o2, o3);
    if (lane == 0) { s_m[w] = m; s_l[w] = l; }
    __syncthreads();
    if (w == 0) {
        float M = s_m[0];
#pragma unroll
        for (int k = 1; k < NW; k++) M = fmaxf(M, s_m[k]);
        float L = 0.f, r = 0.f;
#pragma unroll
        for (int k = 0; k < NW; k++) {
            const float s = ex2(s_m[k] - M);
            L = fmaf(s, s_l[k], L);
            r = fmaf(s, s_o[k * 32 + lane], r);
        }
        P.out[h * D + slice * 32 + lane] = __float2bfloat16(r / L);
        if (lane == 0) asm volatile("red.relaxed.gpu.global.add.u32 [%0], 1;" :: "l"(&g_cnt) : "memory");
    }
}

__global__ void __launch_bounds__(NW * 32, MINB) attn_kernel(const Params P) {
    __shared__ __align__(16) float sm[2 * NW + NW * D];
    uint64_t pol = 0;
    const int b = blockIdx.x;
    int vi;
    if (b < NK) { k_role(P, b / KC_PER_G, b % KC_PER_G, pol); return; }
    vi = b - NK;
    if (vi < H * VSEG) {
        const int h = vi / VSEG, j = vi % VSEG;
        if (j < VC) { v_role(P, h, j, pol, sm); return; }
        if (h >= LAG) r_role(P, h - LAG, j - VC, sm);
    } else {
        const int t = vi - H * VSEG;
        r_role(P, H - LAG + t / RS, t % RS, sm);
    }
}

}

extern "C" void kernel_launch(void* const* d_in, const int* in_sizes, int n_in, void* d_out, int out_size) {
    (void)in_sizes; (void)n_in; (void)out_size;
    Params P;
    P.q = (const __nv_bfloat16*)d_in[0];
    P.qk = (const int4*)d_in[1];
    P.ks = (const __nv_bfloat16*)d_in[2];
    P.kz = (const __nv_bfloat16*)d_in[3];
    P.qv = (const int4*)d_in[4];
    P.vs = (const __nv_bfloat16*)d_in[5];
    P.vz = (const __nv_bfloat16*)d_in[6];
    P.qcos = (const __nv_bfloat16*)d_in[7];
    P.qsin = (const __nv_bfloat16*)d_in[8];
    P.kcos = (const __nv_bfloat16*)d_in[9];
    P.ksin = (const __nv_bfloat16*)d_in[10];
    P.out = (__nv_bfloat16*)d_out;
    attn_kernel<<<GRID, NW * 32>>>(P);
}
```

```cpp
#include <cuda_runtime.h>
#include <cuda_bf16.h>
#include <stdint.h>

#define KU 4
#define VU 4
#define MINB 4
#define ORDER 0
#define SENT 240
#define SPOS 700
#define LH 3
#define NAP 0
#define EVF 0

namespace {

constexpr int H = 32, S = 8192, D = 128;
constexpr int NW = 8;
constexpr int HG = 8;
constexpr int NG = H / HG;
constexpr int KC_PER_G = S / KU;
constexpr int NK = KC_PER_G * NG;
constexpr int VROWS = NW * VU;
constexpr int VC = S / VROWS;
constexpr int FS = 4;
constexpr int NF = H * FS;
constexpr int VSEG = VC + FS;
constexpr int NV = H * VSEG;
constexpr int NPK = VC / 32;
constexpr int SSEG = KC_PER_G + HG;
constexpr int B_S0 = KC_PER_G + SPOS;
constexpr int B_F = NK + H + NV;
constexpr int GRID = B_F + LH * FS;
static_assert(VU == 4, "geometry");
constexpr int SPIN_LIMIT = 1 << 22;

#define MARK(i_)
#define ROLE(x)

__device__ __align__(16) float g_logits[H * S];
__device__ float4 g_part[H * VC * (D / 4)];
__device__ float4 g_wts[H * (S / 4) * 2];
__device__ float2 g_corr[H];
__device__ unsigned g_cnt;

__device__ __forceinline__ int4 ld_stream(const int4* p, uint64_t pol) {
    int4 v;
    asm volatile("ld.global.nc.L1::no_allocate.v4.s32 {%0,%1,%2,%3}, [%4];"
                 : "=r"(v.x), "=r"(v.y), "=r"(v.z), "=r"(v.w) : "l"(p));
    return v;
}
__device__ __forceinline__ uint2 ld_nc8(const void* p) {
    uint2 v;
    asm volatile("ld.global.nc.v2.u32 {%0,%1}, [%2];" : "=r"(v.x), "=r"(v.y) : "l"(p));
    return v;
}
__device__ __forceinline__ uint4 ld_nc16_na(const void* p) {
    uint4 v;
    asm volatile("ld.global.nc.L1::no_allocate.v4.u32 {%0,%1,%2,%3}, [%4];"
                 : "=r"(v.x), "=r"(v.y), "=r"(v.z), "=r"(v.w) : "l"(p));
    return v;
}
__device__ __forceinline__ uint32_t ld_nc2_na(const void* p) {
    uint16_t v;
    asm volatile("ld.global.nc.L1::no_allocate.u16 %0, [%1];" : "=h"(v) : "l"(p));
    return (uint32_t)v;
}
__device__ __forceinline__ uint32_t ld_rlx4(const void* p) {
    uint32_t v;
    asm volatile("ld.relaxed.gpu.global.u32 %0, [%1];" : "=r"(v) : "l"(p) : "memory");
    return v;
}
__device__ __forceinline__ uint2 ld_rlx8(const void* p) {
    uint2 v;
    asm volatile("ld.relaxed.gpu.global.v2.u32 {%0,%1}, [%2];" : "=r"(v.x), "=r"(v.y) : "l"(p) : "memory");
    return v;
}
__device__ __forceinline__ uint4 ld_rlx16(const void* p) {
    uint4 v;
    asm volatile("ld.relaxed.gpu.global.v4.u32 {%0,%1,%2,%3}, [%4];"
                 : "=r"(v.x), "=r"(v.y), "=r"(v.z), "=r"(v.w) : "l"(p) : "memory");
    return v;
}
__device__ __forceinline__ void st_rlx4(void* p, uint32_t v) {
    asm volatile("st.relaxed.gpu.global.u32 [%0], %1;" :: "l"(p), "r"(v) : "memory");
}
__device__ __forceinline__ void st_rlx8(void* p, uint32_t a, uint32_t b) {
    asm volatile("st.relaxed.gpu.global.v2.u32 [%0], {%1,%2};" :: "l"(p), "r"(a), "r"(b) : "memory");
}
__device__ __forceinline__ void st_rlx16(void* p, uint32_t a, uint32_t b, uint32_t c, uint32_t d) {
    asm volatile("st.relaxed.gpu.global.v4.u32 [%0], {%1,%2,%3,%4};" :: "l"(p), "r"(a), "r"(b), "r"(c), "r"(d) : "memory");
}
__device__ __forceinline__ uint32_t bad4(const uint4& v, uint32_t tag) {
    return (v.x ^ tag) | (v.y ^ tag) | (v.z ^ tag) | (v.w ^ tag);
}
__device__ __forceinline__ uint32_t tagf(float x, uint32_t tag) { return (__float_as_uint(x) & ~3u) | tag; }
__device__ __forceinline__ float bf_lo(uint32_t x) { return __uint_as_float(x << 16); }
__device__ __forceinline__ float bf_hi(uint32_t x) { return __uint_as_float(x & 0xffff0000u); }
__device__ __forceinline__ float ex2(float x) { float y; asm("ex2.approx.ftz.f32 %0, %1;" : "=f"(y) : "f"(x)); return y; }
__device__ __forceinline__ uint32_t bf2_mul(uint32_t a, uint32_t b) {
    uint32_t r; asm("mul.rn.bf16x2 %0, %1, %2;" : "=r"(r) : "r"(a), "r"(b)); return r;
}
__device__ __forceinline__ uint32_t bf2_add(uint32_t a, uint32_t b) {
    uint32_t r; asm("add.rn.bf16x2 %0, %1, %2;" : "=r"(r) : "r"(a), "r"(b)); return r;
}

struct Params {
    const __nv_bfloat16* q;
    const int4* qk;
    const __nv_bfloat16* ks;
    const __nv_bfloat16* kz;
    const int4* qv;
    const __nv_bfloat16* vs;
    const __nv_bfloat16* vz;
    const __nv_bfloat16* qcos;
    const __nv_bfloat16* qsin;
    const __nv_bfloat16* kcos;
    const __nv_bfloat16* ksin;
    __nv_bfloat16* out;
};

__device__ __forceinline__ uint32_t read_tag() {
    uint32_t c;
    asm volatile("ld.global.ca.u32 %0, [%1];" : "=r"(c) : "l"(&g_cnt));
    return ((c / NF) + 1u) & 3u;
}

__device__ __forceinline__ void k_role(const Params& P, int g, int rb, uint64_t pol) {
    const int w = threadIdx.x >> 5, lane = threadIdx.x & 31;
    const int h = g * HG + w;
    const int r0 = rb * KU;
    const size_t row = (size_t)h * S + r0;
    int4 kv[KU];
#pragma unroll
    for (int u = 0; u < KU; u++) kv[u] = ld_stream(P.qk + (row + u) * 32 + lane, pol);
    uint2 cs[KU], sn[KU];
#pragma unroll
    for (int u = 0; u < KU; u++) {
        cs[u] = ld_nc8(P.kcos + (size_t)(r0 + u) * D + lane * 4);
        sn[u] = ld_nc8(P.ksin + (size_t)(r0 + u) * D + (lane ^ 16) * 4);
    }
    uint32_t zz[KU], sc[KU];
#pragma unroll
    for (int u = 0; u < KU; u += 4) {
        uint4 a = ld_nc16_na(P.kz + (row + u) * 2);
        uint4 b = ld_nc16_na(P.ks + (row + u) * 2);
        zz[u] = a.x; zz[u + 1] = a.y; zz[u + 2] = a.z; zz[u + 3] = a.w;
        sc[u] = b.x; sc[u + 1] = b.y; sc[u + 2] = b.z; sc[u + 3] = b.w;
    }
    const uint2 qq = ld_nc8(P.q + h * D + lane * 4);
    const uint2 qp = ld_nc8(P.q + h * D + (lane ^ 16) * 4);
    const uint2 qc = ld_nc8(P.qcos + lane * 4);
    const uint2 qs = ld_nc8(P.qsin + lane * 4);
    const uint32_t tag = read_tag();
    const uint32_t neg = (lane < 16) ? 0x80008000u : 0u;
    uint2 qr;
    qr.x = bf2_add(bf2_mul(qq.x, qc.x), bf2_mul(qp.x ^ neg, qs.x));
    qr.y = bf2_add(bf2_mul(qq.y, qc.y), bf2_mul(qp.y ^ neg, qs.y));
    uint2 qo;
    qo.x = __shfl_xor_sync(0xffffffffu, qr.x, 16);
    qo.y = __shfl_xor_sync(0xffffffffu, qr.y, 16);
    const float c = 0.08838834764831845f * 1.4426950408889634f;
    const float cb = (lane < 16) ? c : -c;
    const float qa0 = bf_lo(qr.x) * c, qa1 = bf_hi(qr.x) * c, qa2 = bf_lo(qr.y) * c, qa3 = bf_hi(qr.y) * c;
    const float qb0 = bf_lo(qo.x) * cb, qb1 = bf_hi(qo.x) * cb, qb2 = bf_lo(qo.y) * cb, qb3 = bf_hi(qo.y) * cb;
    const uint32_t sel = (lane < 16) ? 0x1044u : 0x3244u;

    float acc[KU];
#pragma unroll
    for (int u = 0; u < KU; u++) {
        const float z = __uint_as_float(__byte_perm(zz[u], 0u, sel));
        const float s = __uint_as_float(__byte_perm(sc[u], 0u, sel));
        const float a0 = fmaf(qa0, bf_lo(cs[u].x), qb0 * bf_lo(sn[u].x));
        const float a1 = fmaf(qa1, bf_hi(cs[u].x), qb1 * bf_hi(sn[u].x));
        const float a2 = fmaf(qa2, bf_lo(cs[u].y), qb2 * bf_lo(sn[u].y));
        const float a3 = fmaf(qa3, bf_hi(cs[u].y), qb3 * bf_hi(sn[u].y));
        float t = ((float)kv[u].x - z) * a0;
        t = fmaf((float)kv[u].y - z, a1, t);
        t = fmaf((float)kv[u].z - z, a2, t);
        t = fmaf((float)kv[u].w - z, a3, t);
        acc[u] = t * s;
    }
    int idx = 0;
    int off = 16;
#pragma unroll
    for (int n = KU; n > 1; n >>= 1, off >>= 1) {
        const bool up = (lane & off) != 0;
#pragma unroll
        for (int i = 0; i < n / 2; i++) {
            const float keep = up ? acc[i + n / 2] : acc[i];
            const float send = up ? acc[i] : acc[i + n / 2];
            acc[i] = keep + __shfl_xor_sync(0xffffffffu, send, off);
        }
        idx += up ? n / 2 : 0;
    }
#pragma unroll
    for (; off > 0; off >>= 1) acc[0] += __shfl_xor_sync(0xffffffffu, acc[0], off);
    asm volatile("{\n.reg .pred p;\nsetp.eq.u32 p, %2, 0;\n@p st.relaxed.gpu.global.u32 [%0], %1;\n}"
                 :: "l"(g_logits + row + idx), "r"(tagf(acc[0], tag)), "r"(lane & (32 / KU - 1)) : "memory");
}

__device__ __forceinline__ float block_sum(float x, float* s_red) {
#pragma unroll
    for (int o = 1; o < 32; o <<= 1) x += __shfl_xor_sync(0xffffffffu, x, o);
    if ((threadIdx.x & 31) == 0) s_red[threadIdx.x >> 5] = x;
    __syncthreads();
    const float4 a = *(const float4*)(s_red), b = *(const float4*)(s_red + 4);
    return ((a.x + a.y) + (a.z + a.w)) + ((b.x + b.y) + (b.z + b.w));
}

__device__ __forceinline__ void s_role(const Params& P, int h, float* sm) {
    constexpr int NB = S / (4 * NW * 32);
    const int t = threadIdx.x;
    const uint32_t tag = read_tag();
    const float* lp = g_logits + (size_t)h * S + t * 4;
    uint4 lg[NB];
    for (int it = 0;; it++) {
        uint32_t bad = 0;
#pragma unroll
        for (int j = 0; j < NB; j++) lg[j] = ld_rlx16(lp + j * (4 * NW * 32));
#pragma unroll
        for (int j = 0; j < NB; j++) bad |= bad4(lg[j], tag);
        if (!__any_sync(0xffffffffu, bad & 3u)) break;
        if (it > SPIN_LIMIT) __trap();
        __nanosleep(500);
    }
    float m = __uint_as_float(lg[0].x);
#pragma unroll
    for (int j = 0; j < NB; j++)
        m = fmaxf(fmaxf(m, fmaxf(__uint_as_float(lg[j].x), __uint_as_float(lg[j].y))),
                  fmaxf(__uint_as_float(lg[j].z), __uint_as_float(lg[j].w)));
#pragma unroll
    for (int o = 1; o < 32; o <<= 1) m = fmaxf(m, __shfl_xor_sync(0xffffffffu, m, o));
    if ((t & 31) == 0) sm[t >> 5] = m;
    __syncthreads();
    {
        const float4 a = *(const float4*)(sm), b = *(const float4*)(sm + 4);
        m = fmaxf(fmaxf(fmaxf(a.x, a.y), fmaxf(a.z, a.w)), fmaxf(fmaxf(b.x, b.y), fmaxf(b.z, b.w)));
    }
    float p[NB][4];
    float l = 0.f;
#pragma unroll
    for (int j = 0; j < NB; j++) {
        p[j][0] = ex2(__uint_as_float(lg[j].x) - m);
        p[j][1] = ex2(__uint_as_float(lg[j].y) - m);
        p[j][2] = ex2(__uint_as_float(lg[j].z) - m);
        p[j][3] = ex2(__uint_as_float(lg[j].w) - m);
        l += (p[j][0] + p[j][1]) + (p[j][2] + p[j][3]);
    }
    const float inv = 1.f / block_sum(l, sm + NW);
    float c0 = 0.f, c1 = 0.f;
    const size_t row = (size_t)h * S + t * 4;
#pragma unroll
    for (int j0 = 0; j0 < NB; j0 += 2) {
        uint4 sv[2], zv[2];
#pragma unroll
        for (int k = 0; k < 2; k++) {
            sv[k] = ld_nc16_na(P.vs + (row + (j0 + k) * (4 * NW * 32)) * 2);
            zv[k] = ld_nc16_na(P.vz + (row + (j0 + k) * (4 * NW * 32)) * 2);
        }
#pragma unroll
        for (int k = 0; k < 2; k++) {
            const int j = j0 + k;
            const uint32_t sc[4] = {sv[k].x, sv[k].y, sv[k].z, sv[k].w};
            const uint32_t zz[4] = {zv[k].x, zv[k].y, zv[k].z, zv[k].w};
            uint32_t w0[4], w1[4];
#pragma unroll
            for (int i = 0; i < 4; i++) {
                const float pn = p[j][i] * inv;
                w0[i] = tagf(pn * bf_lo(sc[i]), tag);
                w1[i] = tagf(pn * bf_hi(sc[i]), tag);
                c0 = fmaf(__uint_as_float(w0[i]), bf_lo(zz[i]), c0);
                c1 = fmaf(__uint_as_float(w1[i]), bf_hi(zz[i]), c1);
            }
            float4* wp = g_wts + ((size_t)h * (S / 4) + t + j * (NW * 32)) * 2;
            st_rlx16(wp, w0[0], w0[1], w0[2], w0[3]);
            st_rlx16(wp + 1, w1[0], w1[1], w1[2], w1[3]);
        }
    }
    c0 = block_sum(c0, sm + 2 * NW);
    c1 = block_sum(c1, sm + 3 * NW);
    if (t == 0) st_rlx8(g_corr + h, tagf(c0, tag), tagf(c1, tag));
}

__device__ __forceinline__ void v_role(const Params& P, int h, int j, uint64_t pol, float* sm) {
    const int w = threadIdx.x >> 5, lane = threadIdx.x & 31;
    const size_t row = (size_t)h * S + j * VROWS + w * VU;
    int4 vv[VU];
#pragma unroll
    for (int u = 0; u < VU; u++) vv[u] = ld_stream(P.qv + (row + u) * 32 + lane, pol);
    const uint32_t tag = read_tag();
    const float4* wp = g_wts + (row / 4) * 2 + (lane >> 4);
    uint4 wt = ld_rlx16(wp);
    for (int it = 0; bad4(wt, tag) & 3u; it++) {
        if (it > SPIN_LIMIT) __trap();
        __nanosleep(100);
        wt = ld_rlx16(wp);
    }
    const float wu[4] = {__uint_as_float(wt.x), __uint_as_float(wt.y), __uint_as_float(wt.z), __uint_as_float(wt.w)};
    float o0 = (float)vv[0].x * wu[0], o1 = (float)vv[0].y * wu[0], o2 = (float)vv[0].z * wu[0], o3 = (float)vv[0].w * wu[0];
#pragma unroll
    for (int u = 1; u < VU; u++) {
        o0 = fmaf((float)vv[u].x, wu[u], o0);
        o1 = fmaf((float)vv[u].y, wu[u], o1);
        o2 = fmaf((float)vv[u].z, wu[u], o2);
        o3 = fmaf((float)vv[u].w, wu[u], o3);
    }
    *(float4*)(sm + w * D + lane * 4) = make_float4(o0, o1, o2, o3);
    __syncthreads();
    const int t = threadIdx.x;
    if (t < D) {
        float r[NW];
#pragma unroll
        for (int k = 0; k < NW; k++) r[k] = sm[k * D + t];
        const float x = ((r[0] + r[1]) + (r[2] + r[3])) + ((r[4] + r[5]) + (r[6] + r[7]));
        st_rlx4((float*)(g_part + ((size_t)h * VC + j) * (D / 4)) + t, tagf(x, tag));
    }
}

__device__ __forceinline__ void r_role(const Params& P, int h, int slice, float* sm) {
    const int t = threadIdx.x, w = t >> 5, lane = t & 31;
    const int c = t & 7, r = t >> 3;
    const uint32_t tag = read_tag();
    const float* bp = (const float*)(g_corr + h) + (slice >> 1);
    uint32_t base = ld_rlx4(bp);
    {
        const float* sp = (const float*)(g_part + ((size_t)h * VC + SENT + w) * (D / 4));
        for (int it = 0; (ld_rlx4(sp) ^ tag) & 3u; it++) {
            if (it > SPIN_LIMIT) __trap();
        }
    }
    MARK(0);
    const float4* pp = g_part + ((size_t)h * VC + r) * (D / 4) + slice * 8 + c;
    float o0 = 0.f, o1 = 0.f, o2 = 0.f, o3 = 0.f;
    uint32_t todo = (1u << NPK) - 1u;
    for (int it = 0; todo; it++) {
        uint4 pv[NPK];
#pragma unroll
        for (int k = 0; k < NPK; k++)
            if (todo >> k & 1u) pv[k] = ld_rlx16(pp + k * 32 * (D / 4));
#pragma unroll
        for (int k = 0; k < NPK; k++)
            if ((todo >> k & 1u) && !(bad4(pv[k], tag) & 3u)) {
                todo &= ~(1u << k);
                o0 += __uint_as_float(pv[k].x);
                o1 += __uint_as_float(pv[k].y);
                o2 += __uint_as_float(pv[k].z);
                o3 += __uint_as_float(pv[k].w);
            }
        if (it > SPIN_LIMIT) __trap();
        if (NAP && todo) __nanosleep(NAP);
    }
    __syncwarp();
    MARK(1);
    {
        const bool up = (lane & 16) != 0;
        const float a = (up ? o2 : o0) + __shfl_xor_sync(0xffffffffu, up ? o0 : o2, 16);
        const float b = (up ? o3 : o1) + __shfl_xor_sync(0xffffffffu, up ? o1 : o3, 16);
        const bool up2 = (lane & 8) != 0;
        const float x = (up2 ? b : a) + __shfl_xor_sync(0xffffffffu, up2 ? a : b, 8);
        sm[w * 32 + c * 4 + (lane >> 3)] = x;
    }
    if (w == 0) {
        for (int it = 0; (base ^ tag) & 3u; it++) {
            if (it > SPIN_LIMIT) __trap();
            base = ld_rlx4(bp);
        }
    }
    __syncthreads();
    MARK(2);
    if (w == 0) {
        float q[NW];
#pragma unroll
        for (int k = 0; k < NW; k++) q[k] = sm[k * 32 + lane];
        const float x = (((q[0] + q[1]) + (q[2] + q[3])) + ((q[4] + q[5]) + (q[6] + q[7]))) - __uint_as_float(base);
        P.out[h * D + slice * 32 + lane] = __float2bfloat16(x);
        if (lane == 0) asm volatile("red.relaxed.gpu.global.add.u32 [%0], 1;" :: "l"(&g_cnt) : "memory");
    }
}

__global__ void __launch_bounds__(NW * 32, MINB) attn_kernel(const Params P) {
    __shared__ __align__(16) float sm[NW * D];
    uint64_t pol = 0;
    int b = blockIdx.x;
    if (b >= B_S0 && b < B_F) {
        const int g = min((b - B_S0) / SSEG, NG - 1);
        const int y = b - B_S0 - g * SSEG;
        if (y < HG) { ROLE(3); s_role(P, g * HG + y, sm); return; }
        b -= (g + 1) * HG;
    }
    if (b < NK) {
        ROLE(0);
        k_role(P, b / KC_PER_G, b % KC_PER_G, pol);
        return;
    }
    int h, j;
    if (b < B_F) {
        h = (b - NK) / VSEG;
        j = (b - NK) % VSEG;
        if (j < VC) { ROLE(1); v_role(P, h, j, pol, sm); return; }
        ROLE(2);
        h -= LH;
        j -= VC;
        if (h < 0) return;
    } else {
        ROLE(2);
        h = H - LH + (b - B_F) / FS;
        j = (b - B_F) % FS;
    }
    r_role(P, h, j, sm);
}

}

extern "C" void kernel_launch(void* const* d_in, const int* in_sizes, int n_in, void* d_out, int out_size) {
    (void)in_sizes; (void)n_in; (void)out_size;
    Params P;
    P.q = (const __nv_bfloat16*)d_in[0];
    P.qk = (const int4*)d_in[1];
    P.ks = (const __nv_bfloat16*)d_in[2];
    P.kz = (const __nv_bfloat16*)d_in[3];
    P.qv = (const int4*)d_in[4];
    P.vs = (const __nv_bfloat16*)d_in[5];
    P.vz = (const __nv_bfloat16*)d_in[6];
    P.qcos = (const __nv_bfloat16*)d_in[7];
    P.qsin = (const __nv_bfloat16*)d_in[8];
    P.kcos = (const __nv_bfloat16*)d_in[9];
    P.ksin = (const __nv_bfloat16*)d_in[10];
    P.out = (__nv_bfloat16*)d_out;
    attn_kernel<<<GRID, NW * 32>>>(P);
}
```

```cpp
#include <cuda_runtime.h>
#include <cuda_bf16.h>
#include <stdint.h>

#define MINB 4
#define SD 2
#define LH 2
#define NAP 100
#define AS 528
#define NC 2
#define ORD 1

namespace {

constexpr int H = 32, S = 8192, D = 128;
constexpr int NW = 8;
constexpr int NT = NW * 32;
constexpr int U = 4;
constexpr int SEG = S / (NW * U);
constexpr int GX = SEG + 2;
constexpr int GY = 2 * H;
constexpr int GRID = GX * GY;
constexpr int NF = H * 4;
constexpr int CB = 9;
constexpr int SPIN_LIMIT = 1 << 22;

struct Scratch {
    unsigned cnt[256];
    float4 wts[H * (S / 4) * 2];
    float logits[H * S];
    unsigned long long acc[H * NC * (D / 16) * AS];
    float2 corr[H * 2];
};
__device__ __align__(1024) Scratch g_scr;

#define MARK(i_)
#define MARK2(i_)

__device__ __forceinline__ int4 ld_stream(const int4* p) {
    int4 v;
    asm volatile("ld.global.nc.L1::no_allocate.v4.s32 {%0,%1,%2,%3}, [%4];"
                 : "=r"(v.x), "=r"(v.y), "=r"(v.z), "=r"(v.w) : "l"(p));
    return v;
}
__device__ __forceinline__ uint2 ld_nc8(const void* p) {
    uint2 v;
    asm volatile("ld.global.nc.v2.u32 {%0,%1}, [%2];" : "=r"(v.x), "=r"(v.y) : "l"(p));
    return v;
}
__device__ __forceinline__ uint4 ld_nc16(const void* p) {
    uint4 v;
    asm volatile("ld.global.nc.v4.u32 {%0,%1,%2,%3}, [%4];"
                 : "=r"(v.x), "=r"(v.y), "=r"(v.z), "=r"(v.w) : "l"(p));
    return v;
}
__device__ __forceinline__ uint4 ld_nc16_na(const void* p) {
    uint4 v;
    asm volatile("ld.global.nc.L1::no_allocate.v4.u32 {%0,%1,%2,%3}, [%4];"
                 : "=r"(v.x), "=r"(v.y), "=r"(v.z), "=r"(v.w) : "l"(p));
    return v;
}
__device__ __forceinline__ uint2 ld_rlx8(const void* p) {
    uint2 v;
    asm volatile("ld.relaxed.gpu.global.v2.u32 {%0,%1}, [%2];" : "=r"(v.x), "=r"(v.y) : "l"(p) : "memory");
    return v;
}
__device__ __forceinline__ uint4 ld_rlx16(const void* p) {
    uint4 v;
    asm volatile("ld.relaxed.gpu.global.v4.u32 {%0,%1,%2,%3}, [%4];"
                 : "=r"(v.x), "=r"(v.y), "=r"(v.z), "=r"(v.w) : "l"(p) : "memory");
    return v;
}
__device__ __forceinline__ unsigned long long ld_rlx64(const void* p) {
    unsigned long long v;
    asm volatile("ld.relaxed.gpu.global.u64 %0, [%1];" : "=l"(v) : "l"(p) : "memory");
    return v;
}
__device__ __forceinline__ void st_rlx64(void* p, unsigned long long v) {
    asm volatile("st.relaxed.gpu.global.u64 [%0], %1;" :: "l"(p), "l"(v) : "memory");
}
__device__ __forceinline__ void st_rlx8(void* p, uint32_t a, uint32_t b) {
    asm volatile("st.relaxed.gpu.global.v2.u32 [%0], {%1,%2};" :: "l"(p), "r"(a), "r"(b) : "memory");
}
__device__ __forceinline__ void st_rlx16(void* p, uint32_t a, uint32_t b, uint32_t c, uint32_t d) {
    asm volatile("st.relaxed.gpu.global.v4.u32 [%0], {%1,%2,%3,%4};" :: "l"(p), "r"(a), "r"(b), "r"(c), "r"(d) : "memory");
}
__device__ __forceinline__ uint32_t bad4(const uint4& v, uint32_t tag) {
    return (v.x ^ tag) | (v.y ^ tag) | (v.z ^ tag) | (v.w ^ tag);
}
__device__ __forceinline__ uint32_t tagf(float x, uint32_t tag) { return (__float_as_uint(x) & ~3u) | tag; }
__device__ __forceinline__ float bf_lo(uint32_t x) { return __uint_as_float(x << 16); }
__device__ __forceinline__ float bf_hi(uint32_t x) { return __uint_as_float(x & 0xffff0000u); }
__device__ __forceinline__ float ex2(float x) { float y; asm("ex2.approx.ftz.f32 %0, %1;" : "=f"(y) : "f"(x)); return y; }
__device__ __forceinline__ uint32_t bf2_mul(uint32_t a, uint32_t b) {
    uint32_t r; asm("mul.rn.bf16x2 %0, %1, %2;" : "=r"(r) : "r"(a), "r"(b)); return r;
}
__device__ __forceinline__ uint32_t bf2_add(uint32_t a, uint32_t b) {
    uint32_t r; asm("add.rn.bf16x2 %0, %1, %2;" : "=r"(r) : "r"(a), "r"(b)); return r;
}

struct Params {
    const int4* qk;
    const int4* qv;
    Scratch* scr;
    const __nv_bfloat16* q;
    const __nv_bfloat16* qcos;
    const __nv_bfloat16* qsin;
    const __nv_bfloat16* kcos;
    const __nv_bfloat16* ksin;
    const __nv_bfloat16* ks;
    const __nv_bfloat16* kz;
    const __nv_bfloat16* vs;
    const __nv_bfloat16* vz;
    __nv_bfloat16* out;
};

__device__ __forceinline__ unsigned long long* acc_ptr(const Params& P, int hc, int col) {
    return P.scr->acc + (uint32_t)((hc * (D / 16) + (col >> 4)) * AS + (col & 15));
}
__device__ __forceinline__ uint32_t ld_cnt(const Params& P) {
    uint32_t c;
    asm volatile("ld.global.ca.u32 %0, [%1];" : "=r"(c) : "l"(P.scr->cnt));
    return c;
}
__device__ __forceinline__ uint32_t tag_of(uint32_t c) { return ((c / NF) + 1u) & 3u; }

#define SPLIT(p_) do { if ((p_) == nullptr) __trap(); } while (0)
__device__ __forceinline__ void k_role(const Params& P, uint32_t x, uint32_t y) {
    const uint32_t w = threadIdx.x >> 5, lane = threadIdx.x & 31;
    const uint32_t h = (y & 24u) + w, r0 = ((y & 7u) * SEG + x) * U;
    const uint32_t row = h * S + r0;
    const uint32_t cnt = ld_cnt(P);
    const uint2 qq = ld_nc8(P.q + (h * D + lane * 4));
    const uint2 qp = ld_nc8(P.q + (h * D + (lane ^ 16) * 4));
    const uint2 qc = ld_nc8(P.qcos + lane * 4);
    const uint2 qs = ld_nc8(P.qsin + lane * 4);
    int4 kv[U];
    const int4* src = P.qk + (row * 32 + lane);
    SPLIT(P.qk);
#pragma unroll
    for (int u = 0; u < U; u++) kv[u] = ld_stream(src + u * 32);
    SPLIT(P.kcos);
    uint2 cs[U], sn[U];
    const __nv_bfloat16* cp = P.kcos + (r0 * D + lane * 4);
    const __nv_bfloat16* sp = P.ksin + (r0 * D + (lane ^ 16) * 4);
#pragma unroll
    for (int u = 0; u < U; u++) {
        cs[u] = ld_nc8(cp + u * D);
        sn[u] = ld_nc8(sp + u * D);
    }
    const uint4 z4 = ld_nc16_na(P.kz + row * 2);
    const uint4 s4 = ld_nc16_na(P.ks + row * 2);
    const uint32_t zz[U] = {z4.x, z4.y, z4.z, z4.w}, sc[U] = {s4.x, s4.y, s4.z, s4.w};
    const uint32_t neg = (lane < 16) ? 0x80008000u : 0u;
    uint2 qr;
    qr.x = bf2_add(bf2_mul(qq.x, qc.x), bf2_mul(qp.x ^ neg, qs.x));
    qr.y = bf2_add(bf2_mul(qq.y, qc.y), bf2_mul(qp.y ^ neg, qs.y));
    uint2 qo;
    qo.x = __shfl_xor_sync(0xffffffffu, qr.x, 16);
    qo.y = __shfl_xor_sync(0xffffffffu, qr.y, 16);
    const float c = 0.08838834764831845f * 1.4426950408889634f;
    const float cb = (lane < 16) ? c : -c;
    const float qa0 = bf_lo(qr.x) * c, qa1 = bf_hi(qr.x) * c, qa2 = bf_lo(qr.y) * c, qa3 = bf_hi(qr.y) * c;
    const float qb0 = bf_lo(qo.x) * cb, qb1 = bf_hi(qo.x) * cb, qb2 = bf_lo(qo.y) * cb, qb3 = bf_hi(qo.y) * cb;
    const uint32_t sel = (lane < 16) ? 0x1044u : 0x3244u;

    float acc[U];
#pragma unroll
    for (int u = 0; u < U; u++) {
        const float z = __uint_as_float(__byte_perm(zz[u], 0u, sel));
        const float s = __uint_as_float(__byte_perm(sc[u], 0u, sel));
        const float a0 = fmaf(qa0, bf_lo(cs[u].x), qb0 * bf_lo(sn[u].x));
        const float a1 = fmaf(qa1, bf_hi(cs[u].x), qb1 * bf_hi(sn[u].x));
        const float a2 = fmaf(qa2, bf_lo(cs[u].y), qb2 * bf_lo(sn[u].y));
        const float a3 = fmaf(qa3, bf_hi(cs[u].y), qb3 * bf_hi(sn[u].y));
        float t = ((float)kv[u].x - z) * a0;
        t = fmaf((float)kv[u].y - z, a1, t);
        t = fmaf((float)kv[u].z - z, a2, t);
        t = fmaf((float)kv[u].w - z, a3, t);
        acc[u] = t * s;
    }
    const bool up = (lane & 16) != 0, up2 = (lane & 8) != 0;
    const float a = (up ? acc[2] : acc[0]) + __shfl_xor_sync(0xffffffffu, up ? acc[0] : acc[2], 16);
    const float b = (up ? acc[3] : acc[1]) + __shfl_xor_sync(0xffffffffu, up ? acc[1] : acc[3], 16);
    float lg = (up2 ? b : a) + __shfl_xor_sync(0xffffffffu, up2 ? a : b, 8);
#pragma unroll
    for (int off = 4; off > 0; off >>= 1) lg += __shfl_xor_sync(0xffffffffu, lg, off);
    asm volatile("{\n.reg .pred p;\nsetp.eq.u32 p, %2, 0;\n@p st.relaxed.gpu.global.u32 [%0], %1;\n}"
                 :: "l"(P.scr->logits + (row + (lane >> 3))), "r"(tagf(lg, tag_of(cnt))), "r"(lane & 7) : "memory");
}

__device__ __forceinline__ float block_sum(float x, float* s_red) {
#pragma unroll
    for (int o = 1; o < 32; o <<= 1) x += __shfl_xor_sync(0xffffffffu, x, o);
    if ((threadIdx.x & 31) == 0) s_red[threadIdx.x >> 5] = x;
    __syncthreads();
    const float4 a = *(const float4*)(s_red), b = *(const float4*)(s_red + 4);
    return ((a.x + a.y) + (a.z + a.w)) + ((b.x + b.y) + (b.z + b.w));
}

__device__ __forceinline__ void s_role(const Params& P, int h, float* sm) {
    constexpr int NB = S / (4 * NT);
    const int t = threadIdx.x;
    const uint32_t tag = tag_of(ld_cnt(P));
#pragma unroll
    for (int i = 0; i < (NC * D + NT - 1) / NT; i++)
        if (t + i * NT < NC * D) st_rlx64(acc_ptr(P, h * NC + (t + i * NT) / D, t % D), 0ull);
    __threadfence();
    const float* lp = P.scr->logits + (h * S + t * 4);
    uint4 lg[NB];
    for (int it = 0;; it++) {
        uint32_t bad = 0;
#pragma unroll
        for (int j = 0; j < NB; j++) lg[j] = ld_rlx16(lp + j * (4 * NT));
#pragma unroll
        for (int j = 0; j < NB; j++) bad |= bad4(lg[j], tag);
        if (!__any_sync(0xffffffffu, bad & 3u)) break;
        if (it > SPIN_LIMIT) __trap();
        __nanosleep(500);
    }
    float m = __uint_as_float(lg[0].x);
#pragma unroll
    for (int j = 0; j < NB; j++)
        m = fmaxf(fmaxf(m, fmaxf(__uint_as_float(lg[j].x), __uint_as_float(lg[j].y))),
                  fmaxf(__uint_as_float(lg[j].z), __uint_as_float(lg[j].w)));
#pragma unroll
    for (int o = 1; o < 32; o <<= 1) m = fmaxf(m, __shfl_xor_sync(0xffffffffu, m, o));
    if ((t & 31) == 0) sm[t >> 5] = m;
    __syncthreads();
    {
        const float4 a = *(const float4*)(sm), b = *(const float4*)(sm + 4);
        m = fmaxf(fmaxf(fmaxf(a.x, a.y), fmaxf(a.z, a.w)), fmaxf(fmaxf(b.x, b.y), fmaxf(b.z, b.w)));
    }
    float p[NB][4];
    float l = 0.f;
#pragma unroll
    for (int j = 0; j < NB; j++) {
        p[j][0] = ex2(__uint_as_float(lg[j].x) - m);
        p[j][1] = ex2(__uint_as_float(lg[j].y) - m);
        p[j][2] = ex2(__uint_as_float(lg[j].z) - m);
        p[j][3] = ex2(__uint_as_float(lg[j].w) - m);
        l += (p[j][0] + p[j][1]) + (p[j][2] + p[j][3]);
    }
    const float inv = 1.f / block_sum(l, sm + NW);
    const __nv_bfloat16* vsp = P.vs + (h * S + t * 4) * 2;
    const __nv_bfloat16* vzp = P.vz + (h * S + t * 4) * 2;
    float a0 = 0.f, a1 = 0.f;
#pragma unroll
    for (int j0 = 0; j0 < NB; j0 += 4) {
        uint4 sv[4];
#pragma unroll
        for (int k = 0; k < 4; k++) sv[k] = ld_nc16(vsp + (j0 + k) * (8 * NT));
#pragma unroll
        for (int k = 0; k < 4; k++) {
            const uint32_t sc[4] = {sv[k].x, sv[k].y, sv[k].z, sv[k].w};
#pragma unroll
            for (int i = 0; i < 4; i++) {
                a0 = fmaf(p[j0 + k][i], fabsf(bf_lo(sc[i])), a0);
                a1 = fmaf(p[j0 + k][i], fabsf(bf_hi(sc[i])), a1);
            }
        }
    }
    const uint32_t e0 = min(max(__float_as_uint(block_sum(a0 * inv, sm + 2 * NW)) >> 23, 22u), 254u);
    const uint32_t e1 = min(max(__float_as_uint(block_sum(a1 * inv, sm + 3 * NW)) >> 23, 22u), 254u);
    const float i0 = inv * __uint_as_float((275u - e0) << 23), i1 = inv * __uint_as_float((275u - e1) << 23);
    float c0 = 0.f, c1 = 0.f;
    float4* wp = P.scr->wts + (h * (S / 4) + t) * 2;
#pragma unroll
    for (int j0 = 0; j0 < NB; j0 += 2) {
        uint4 sv[2], zv[2];
#pragma unroll
        for (int k = 0; k < 2; k++) {
            sv[k] = ld_nc16(vsp + (j0 + k) * (8 * NT));
            zv[k] = ld_nc16_na(vzp + (j0 + k) * (8 * NT));
        }
#pragma unroll
        for (int k = 0; k < 2; k++) {
            const int j = j0 + k;
            const uint32_t sc[4] = {sv[k].x, sv[k].y, sv[k].z, sv[k].w};
            const uint32_t zz[4] = {zv[k].x, zv[k].y, zv[k].z, zv[k].w};
            uint32_t w0[4], w1[4];
#pragma unroll
            for (int i = 0; i < 4; i++) {
                w0[i] = tagf(p[j][i] * i0 * bf_lo(sc[i]), tag);
                w1[i] = tagf(p[j][i] * i1 * bf_hi(sc[i]), tag);
                c0 = fmaf(__uint_as_float(w0[i]), bf_lo(zz[i]), c0);
                c1 = fmaf(__uint_as_float(w1[i]), bf_hi(zz[i]), c1);
            }
            st_rlx16(wp + j * (2 * NT), w0[0], w0[1], w0[2], w0[3]);
            st_rlx16(wp + j * (2 * NT) + 1, w1[0], w1[1], w1[2], w1[3]);
        }
    }
    c0 = block_sum(c0, sm + 4 * NW);
    c1 = block_sum(c1, sm + 5 * NW);
    if (t == 0) {
        st_rlx8(P.scr->corr + h * 2, tagf(c0, tag), ((e0 - 21u) << 23) | tag);
        st_rlx8(P.scr->corr + h * 2 + 1, tagf(c1, tag), ((e1 - 21u) << 23) | tag);
    }
}

__device__ __forceinline__ uint2 wait_corr(const float2* cp, uint2 cu, uint32_t tag) {
    for (int it = 0; ((cu.x ^ tag) | (cu.y ^ tag)) & 3u; it++) {
        if (it > SPIN_LIMIT) __trap();
        __nanosleep(100);
        cu = ld_rlx8(cp);
    }
    return cu;
}

__device__ __forceinline__ void finish(const Params& P, int e, unsigned long long tot, uint2 cu) {
    const float x = (__ll2float_rn((long long)tot >> CB) - __uint_as_float(cu.x)) * __uint_as_float(cu.y & ~3u);
    P.out[e] = __float2bfloat16(x);
    if ((e & 31) == 0) asm volatile("red.relaxed.gpu.global.add.u32 [%0], 1;" :: "l"(P.scr->cnt) : "memory");
}

template <bool LAST>
__device__ __forceinline__ void v_role(const Params& P, uint32_t x, uint32_t h, float* sm) {
    const int t = threadIdx.x, w = t >> 5, lane = t & 31;
    const uint32_t row = h * S + (x * NW + w) * U;
    int4 vv[U];
    const int4* src = P.qv + (row * 32 + lane);
#pragma unroll
    for (int u = 0; u < U; u++) vv[u] = ld_stream(src + u * 32);
    const float4* wp = P.scr->wts + (row / 2 + (lane >> 4));
    uint4 wt = ld_rlx16(wp);
    const float2* cp = P.scr->corr + (h * 2 + ((t >> 6) & 1));
    uint2 cu;
    if (LAST) cu = ld_rlx8(cp);
    const uint32_t tag = tag_of(ld_cnt(P));
    for (int it = 0; bad4(wt, tag) & 3u; it++) {
        if (it > SPIN_LIMIT) __trap();
        __nanosleep(100);
        wt = ld_rlx16(wp);
    }
    if (LAST) cu = wait_corr(cp, cu, tag);
    const float wu[4] = {__uint_as_float(wt.x), __uint_as_float(wt.y), __uint_as_float(wt.z), __uint_as_float(wt.w)};
    float o0 = (float)vv[0].x * wu[0], o1 = (float)vv[0].y * wu[0], o2 = (float)vv[0].z * wu[0], o3 = (float)vv[0].w * wu[0];
#pragma unroll
    for (int u = 1; u < U; u++) {
        o0 = fmaf((float)vv[u].x, wu[u], o0);
        o1 = fmaf((float)vv[u].y, wu[u], o1);
        o2 = fmaf((float)vv[u].z, wu[u], o2);
        o3 = fmaf((float)vv[u].w, wu[u], o3);
    }
    *(float4*)(sm + w * D + lane * 4) = make_float4(o0, o1, o2, o3);
    __syncthreads();
    if (t < D) {
        float r[NW];
#pragma unroll
        for (int k = 0; k < NW; k++) r[k] = sm[k * D + t];
        const float o = ((r[0] + r[1]) + (r[2] + r[3])) + ((r[4] + r[5]) + (r[6] + r[7]));
        const unsigned long long v = ((unsigned long long)__float2ll_rn(o) << CB) + 1ull;
        if (LAST) {
            unsigned long long old;
            asm volatile("atom.relaxed.gpu.global.add.u64 %0, [%1], %2;" : "=l"(old) : "l"(acc_ptr(P, h * NC, t)), "l"(v) : "memory");
            if (((uint32_t)old & ((1u << CB) - 1u)) == SEG - 1) finish(P, h * D + t, old + v, cu);
        } else {
            asm volatile("red.relaxed.gpu.global.add.u64 [%0], %1;" :: "l"(acc_ptr(P, h * NC + x % NC, t)), "l"(v) : "memory");
        }
    }
}

__device__ __forceinline__ void r_role(const Params& P, int h) {
    const int t = threadIdx.x;
    if (t >= D) return;
    const uint32_t tag = tag_of(ld_cnt(P));
    const float2* cp = P.scr->corr + (h * 2 + (t >> 6));
    const uint2 cu = wait_corr(cp, ld_rlx8(cp), tag);
    __threadfence();
    unsigned long long a;
    for (int it = 0;; it++) {
        a = 0;
#pragma unroll
        for (int c = 0; c < NC; c++) a += ld_rlx64(acc_ptr(P, h * NC + c, t));
        if (((uint32_t)a & ((1u << CB) - 1u)) == SEG) break;
        if (it > SPIN_LIMIT) __trap();
        __nanosleep(NAP);
    }
    finish(P, h * D + t, a, cu);
}

__global__ void __launch_bounds__(NT, MINB) attn_kernel(const Params P) {
    __shared__ __align__(16) float sm[NW * D];
    const uint32_t x = blockIdx.x, y = blockIdx.y;
    if (x >= SEG) {
        if (x == SEG) {
            const int h = (int)y - (NW + SD);
            if (h >= 0 && h < H) s_role(P, h, sm);
        } else {
            if (y >= H + LH) r_role(P, y - (H + LH));
        }
        return;
    }
    if (y >= H) {
        if (y >= GY - LH) v_role<true>(P, x, y - H, sm);
        else v_role<false>(P, x, y - H, sm);
        return;
    }
    k_role(P, x, y);
}

}

extern "C" void kernel_launch(void* const* d_in, const int* in_sizes, int n_in, void* d_out, int out_size) {
    (void)in_sizes; (void)n_in; (void)out_size;
    Params P;
    P.q = (const __nv_bfloat16*)d_in[0];
    P.qk = (const int4*)d_in[1];
    P.ks = (const __nv_bfloat16*)d_in[2];
    P.kz = (const __nv_bfloat16*)d_in[3];
    P.qv = (const int4*)d_in[4];
    P.vs = (const __nv_bfloat16*)d_in[5];
    P.vz = (const __nv_bfloat16*)d_in[6];
    P.qcos = (const __nv_bfloat16*)d_in[7];
    P.qsin = (const __nv_bfloat16*)d_in[8];
    P.kcos = (const __nv_bfloat16*)d_in[9];
    P.ksin = (const __nv_bfloat16*)d_in[10];
    P.out = (__nv_bfloat16*)d_out;
    void* scr = nullptr;
    cudaGetSymbolAddress(&scr, g_scr);
    P.scr = (Scratch*)scr;
    attn_kernel<<<dim3(GX, GY), NT>>>(P);
}
```

```cpp
#include <cuda_runtime.h>
#include <cuda_bf16.h>
#include <stdint.h>

namespace {

constexpr int H = 32, S = 8192, D = 128;
constexpr int NW = 8;
constexpr int NT = NW * 32;
constexpr int U = 4;
constexpr int SEG = S / (NW * U);
constexpr int GX = SEG + 1;
constexpr int SD = 2;
constexpr int FC = 32;
constexpr int FU = 8;
constexpr int NBT = 2;
constexpr int NC = 4;
constexpr int AS = 528;
constexpr int LPR = FC / 4;
constexpr int FB = (NW - 1) * (32 / LPR) * FU;
constexpr int FR = FB * NBT;
constexpr int EARLY = SEG - FR / (NW * U);
constexpr int NF = H * (D / FC);
constexpr int GY = H + (H * EARLY + NF + SEG - 1) / SEG;
constexpr int CB = 10;
static_assert(FR % (NW * U) == 0 && EARLY / NC < 255 && H + NW + SD <= GY, "layout");
constexpr int SPIN_LIMIT = 1 << 22;

struct Scratch {
    unsigned cnt[256];
    float4 wts[H * (S / 4) * 2];
    float logits[H * S];
    unsigned long long acc[H * NC * (D / 16) * AS];
    float2 corr[H * 2];
};
__device__ __align__(1024) Scratch g_scr;

__device__ __forceinline__ int4 ld_stream(const int4* p) {
    int4 v;
    asm volatile("ld.global.nc.L1::no_allocate.v4.s32 {%0,%1,%2,%3}, [%4];"
                 : "=r"(v.x), "=r"(v.y), "=r"(v.z), "=r"(v.w) : "l"(p));
    return v;
}
__device__ __forceinline__ uint2 ld_nc8(const void* p) {
    uint2 v;
    asm volatile("ld.global.nc.v2.u32 {%0,%1}, [%2];" : "=r"(v.x), "=r"(v.y) : "l"(p));
    return v;
}
__device__ __forceinline__ uint4 ld_nc16(const void* p) {
    uint4 v;
    asm volatile("ld.global.nc.v4.u32 {%0,%1,%2,%3}, [%4];"
                 : "=r"(v.x), "=r"(v.y), "=r"(v.z), "=r"(v.w) : "l"(p));
    return v;
}
__device__ __forceinline__ uint4 ld_nc16_na(const void* p) {
    uint4 v;
    asm volatile("ld.global.nc.L1::no_allocate.v4.u32 {%0,%1,%2,%3}, [%4];"
                 : "=r"(v.x), "=r"(v.y), "=r"(v.z), "=r"(v.w) : "l"(p));
    return v;
}
__device__ __forceinline__ uint2 ld_rlx8(const void* p) {
    uint2 v;
    asm volatile("ld.relaxed.gpu.global.v2.u32 {%0,%1}, [%2];" : "=r"(v.x), "=r"(v.y) : "l"(p) : "memory");
    return v;
}
__device__ __forceinline__ uint4 ld_rlx16(const void* p) {
    uint4 v;
    asm volatile("ld.relaxed.gpu.global.v4.u32 {%0,%1,%2,%3}, [%4];"
                 : "=r"(v.x), "=r"(v.y), "=r"(v.z), "=r"(v.w) : "l"(p) : "memory");
    return v;
}
__device__ __forceinline__ unsigned long long ld_rlx64(const void* p) {
    unsigned long long v;
    asm volatile("ld.relaxed.gpu.global.u64 %0, [%1];" : "=l"(v) : "l"(p) : "memory");
    return v;
}
__device__ __forceinline__ void st_rlx64(void* p, unsigned long long v) {
    asm volatile("st.relaxed.gpu.global.u64 [%0], %1;" :: "l"(p), "l"(v) : "memory");
}
__device__ __forceinline__ void st_rlx8(void* p, uint32_t a, uint32_t b) {
    asm volatile("st.relaxed.gpu.global.v2.u32 [%0], {%1,%2};" :: "l"(p), "r"(a), "r"(b) : "memory");
}
__device__ __forceinline__ void st_rlx16(void* p, uint32_t a, uint32_t b, uint32_t c, uint32_t d) {
    asm volatile("st.relaxed.gpu.global.v4.u32 [%0], {%1,%2,%3,%4};" :: "l"(p), "r"(a), "r"(b), "r"(c), "r"(d) : "memory");
}
__device__ __forceinline__ uint32_t bad4(const uint4& v, uint32_t tag) {
    return (v.x ^ tag) | (v.y ^ tag) | (v.z ^ tag) | (v.w ^ tag);
}
__device__ __forceinline__ uint32_t tagf(float x, uint32_t tag) { return (__float_as_uint(x) & ~3u) | tag; }
__device__ __forceinline__ float bf_lo(uint32_t x) { return __uint_as_float(x << 16); }
__device__ __forceinline__ float bf_hi(uint32_t x) { return __uint_as_float(x & 0xffff0000u); }
__device__ __forceinline__ float ex2(float x) { float y; asm("ex2.approx.ftz.f32 %0, %1;" : "=f"(y) : "f"(x)); return y; }
__device__ __forceinline__ uint32_t bf2_mul(uint32_t a, uint32_t b) {
    uint32_t r; asm("mul.rn.bf16x2 %0, %1, %2;" : "=r"(r) : "r"(a), "r"(b)); return r;
}
__device__ __forceinline__ uint32_t bf2_add(uint32_t a, uint32_t b) {
    uint32_t r; asm("add.rn.bf16x2 %0, %1, %2;" : "=r"(r) : "r"(a), "r"(b)); return r;
}

struct Params {
    const int4* qk;
    const int4* qv;
    Scratch* scr;
    const __nv_bfloat16* q;
    const __nv_bfloat16* qcos;
    const __nv_bfloat16* qsin;
    const __nv_bfloat16* kcos;
    const __nv_bfloat16* ksin;
    const __nv_bfloat16* ks;
    const __nv_bfloat16* kz;
    const __nv_bfloat16* vs;
    const __nv_bfloat16* vz;
    __nv_bfloat16* out;
};

__device__ __forceinline__ unsigned long long* acc_ptr(const Params& P, int hc, int col) {
    return P.scr->acc + (uint32_t)((hc * (D / 16) + (col >> 4)) * AS + (col & 15));
}
__device__ __forceinline__ uint32_t ld_cnt(const Params& P) {
    uint32_t c;
    asm volatile("ld.global.ca.u32 %0, [%1];" : "=r"(c) : "l"(P.scr->cnt));
    return c;
}
__device__ __forceinline__ uint32_t tag_of(uint32_t c) { return ((c / NF) + 1u) & 3u; }

#define SPLIT(p_) do { if ((p_) == nullptr) __trap(); } while (0)
__device__ __forceinline__ void k_role(const Params& P, uint32_t x, uint32_t y) {
    const uint32_t w = threadIdx.x >> 5, lane = threadIdx.x & 31;
    const uint32_t h = (y & 24u) + w, r0 = ((y & 7u) * SEG + x) * U;
    const uint32_t row = h * S + r0;
    const uint32_t cnt = ld_cnt(P);
    const uint2 qq = ld_nc8(P.q + (h * D + lane * 4));
    const uint2 qp = ld_nc8(P.q + (h * D + (lane ^ 16) * 4));
    const uint2 qc = ld_nc8(P.qcos + lane * 4);
    const uint2 qs = ld_nc8(P.qsin + lane * 4);
    int4 kv[U];
    const int4* src = P.qk + (row * 32 + lane);
    SPLIT(P.qk);
#pragma unroll
    for (int u = 0; u < U; u++) kv[u] = ld_stream(src + u * 32);
    SPLIT(P.kcos);
    uint2 cs[U], sn[U];
    const __nv_bfloat16* cp = P.kcos + (r0 * D + lane * 4);
    const __nv_bfloat16* sp = P.ksin + (r0 * D + (lane ^ 16) * 4);
#pragma unroll
    for (int u = 0; u < U; u++) {
        cs[u] = ld_nc8(cp + u * D);
        sn[u] = ld_nc8(sp + u * D);
    }
    const uint4 z4 = ld_nc16_na(P.kz + row * 2);
    const uint4 s4 = ld_nc16_na(P.ks + row * 2);
    const uint32_t zz[U] = {z4.x, z4.y, z4.z, z4.w}, sc[U] = {s4.x, s4.y, s4.z, s4.w};
    const uint32_t neg = (lane < 16) ? 0x80008000u : 0u;
    uint2 qr;
    qr.x = bf2_add(bf2_mul(qq.x, qc.x), bf2_mul(qp.x ^ neg, qs.x));
    qr.y = bf2_add(bf2_mul(qq.y, qc.y), bf2_mul(qp.y ^ neg, qs.y));
    uint2 qo;
    qo.x = __shfl_xor_sync(0xffffffffu, qr.x, 16);
    qo.y = __shfl_xor_sync(0xffffffffu, qr.y, 16);
    const float c = 0.08838834764831845f * 1.4426950408889634f;
    const float cb = (lane < 16) ? c : -c;
    const float qa0 = bf_lo(qr.x) * c, qa1 = bf_hi(qr.x) * c, qa2 = bf_lo(qr.y) * c, qa3 = bf_hi(qr.y) * c;
    const float qb0 = bf_lo(qo.x) * cb, qb1 = bf_hi(qo.x) * cb, qb2 = bf_lo(qo.y) * cb, qb3 = bf_hi(qo.y) * cb;
    const uint32_t sel = (lane < 16) ? 0x1044u : 0x3244u;

    float acc[U];
#pragma unroll
    for (int u = 0; u < U; u++) {
        const float z = __uint_as_float(__byte_perm(zz[u], 0u, sel));
        const float s = __uint_as_float(__byte_perm(sc[u], 0u, sel));
        const float a0 = fmaf(qa0, bf_lo(cs[u].x), qb0 * bf_lo(sn[u].x));
        const float a1 = fmaf(qa1, bf_hi(cs[u].x), qb1 * bf_hi(sn[u].x));
        const float a2 = fmaf(qa2, bf_lo(cs[u].y), qb2 * bf_lo(sn[u].y));
        const float a3 = fmaf(qa3, bf_hi(cs[u].y), qb3 * bf_hi(sn[u].y));
        float t = ((float)kv[u].x - z) * a0;
        t = fmaf((float)kv[u].y - z, a1, t);
        t = fmaf((float)kv[u].z - z, a2, t);
        t = fmaf((float)kv[u].w - z, a3, t);
        acc[u] = t * s;
    }
    const bool up = (lane & 16) != 0, up2 = (lane & 8) != 0;
    const float a = (up ? acc[2] : acc[0]) + __shfl_xor_sync(0xffffffffu, up ? acc[0] : acc[2], 16);
    const float b = (up ? acc[3] : acc[1]) + __shfl_xor_sync(0xffffffffu, up ? acc[1] : acc[3], 16);
    float lg = (up2 ? b : a) + __shfl_xor_sync(0xffffffffu, up2 ? a : b, 8);
#pragma unroll
    for (int off = 4; off > 0; off >>= 1) lg += __shfl_xor_sync(0xffffffffu, lg, off);
    asm volatile("{\n.reg .pred p;\nsetp.eq.u32 p, %2, 0;\n@p st.relaxed.gpu.global.u32 [%0], %1;\n}"
                 :: "l"(P.scr->logits + (row + (lane >> 3))), "r"(tagf(lg, tag_of(cnt))), "r"(lane & 7) : "memory");
}

__device__ __forceinline__ float block_sum(float x, float* s_red) {
#pragma unroll
    for (int o = 1; o < 32; o <<= 1) x += __shfl_xor_sync(0xffffffffu, x, o);
    if ((threadIdx.x & 31) == 0) s_red[threadIdx.x >> 5] = x;
    __syncthreads();
    const float4 a = *(const float4*)(s_red), b = *(const float4*)(s_red + 4);
    return ((a.x + a.y) + (a.z + a.w)) + ((b.x + b.y) + (b.z + b.w));
}

__device__ __forceinline__ void s_role(const Params& P, int h, float* sm) {
    constexpr int NB = S / (4 * NT);
    const int t = threadIdx.x;
    const uint32_t tag = tag_of(ld_cnt(P));
#pragma unroll
    for (int i = 0; i < (NC * D + NT - 1) / NT; i++)
        if (t + i * NT < NC * D) st_rlx64(acc_ptr(P, h * NC + (t + i * NT) / D, t % D), tag << 8);
    __threadfence();
    const float* lp = P.scr->logits + (h * S + t * 4);
    uint4 lg[NB];
    for (int it = 0;; it++) {
        uint32_t bad = 0;
#pragma unroll
        for (int j = 0; j < NB; j++) lg[j] = ld_rlx16(lp + j * (4 * NT));
#pragma unroll
        for (int j = 0; j < NB; j++) bad |= bad4(lg[j], tag);
        if (!__any_sync(0xffffffffu, bad & 3u)) break;
        if (it > SPIN_LIMIT) __trap();
        __nanosleep(500);
    }
    float m = __uint_as_float(lg[0].x);
#pragma unroll
    for (int j = 0; j < NB; j++)
        m = fmaxf(fmaxf(m, fmaxf(__uint_as_float(lg[j].x), __uint_as_float(lg[j].y))),
                  fmaxf(__uint_as_float(lg[j].z), __uint_as_float(lg[j].w)));
#pragma unroll
    for (int o = 1; o < 32; o <<= 1) m = fmaxf(m, __shfl_xor_sync(0xffffffffu, m, o));
    if ((t & 31) == 0) sm[t >> 5] = m;
    __syncthreads();
    {
        const float4 a = *(const float4*)(sm), b = *(const float4*)(sm + 4);
        m = fmaxf(fmaxf(fmaxf(a.x, a.y), fmaxf(a.z, a.w)), fmaxf(fmaxf(b.x, b.y), fmaxf(b.z, b.w)));
    }
    float p[NB][4];
    float l = 0.f;
#pragma unroll
    for (int j = 0; j < NB; j++) {
        p[j][0] = ex2(__uint_as_float(lg[j].x) - m);
        p[j][1] = ex2(__uint_as_float(lg[j].y) - m);
        p[j][2] = ex2(__uint_as_float(lg[j].z) - m);
        p[j][3] = ex2(__uint_as_float(lg[j].w) - m);
        l += (p[j][0] + p[j][1]) + (p[j][2] + p[j][3]);
    }
    const float inv = 1.f / block_sum(l, sm + NW);
    const __nv_bfloat16* vsp = P.vs + (h * S + t * 4) * 2;
    const __nv_bfloat16* vzp = P.vz + (h * S + t * 4) * 2;
    float a0 = 0.f, a1 = 0.f;
#pragma unroll
    for (int j0 = 0; j0 < NB; j0 += 4) {
        uint4 sv[4];
#pragma unroll
        for (int k = 0; k < 4; k++) sv[k] = ld_nc16(vsp + (j0 + k) * (8 * NT));
#pragma unroll
        for (int k = 0; k < 4; k++) {
            const uint32_t sc[4] = {sv[k].x, sv[k].y, sv[k].z, sv[k].w};
#pragma unroll
            for (int i = 0; i < 4; i++) {
                a0 = fmaf(p[j0 + k][i], fabsf(bf_lo(sc[i])), a0);
                a1 = fmaf(p[j0 + k][i], fabsf(bf_hi(sc[i])), a1);
            }
        }
    }
    const uint32_t e0 = min(max(__float_as_uint(block_sum(a0 * inv, sm + 2 * NW)) >> 23, 22u), 254u);
    const uint32_t e1 = min(max(__float_as_uint(block_sum(a1 * inv, sm + 3 * NW)) >> 23, 22u), 254u);
    const float i0 = inv * __uint_as_float((274u - e0) << 23), i1 = inv * __uint_as_float((274u - e1) << 23);
    float c0 = 0.f, c1 = 0.f;
    float4* wp = P.scr->wts + (h * (S / 4) + t) * 2;
#pragma unroll
    for (int j0 = 0; j0 < NB; j0 += 2) {
        uint4 sv[2], zv[2];
#pragma unroll
        for (int k = 0; k < 2; k++) {
            sv[k] = ld_nc16(vsp + (j0 + k) * (8 * NT));
            zv[k] = ld_nc16_na(vzp + (j0 + k) * (8 * NT));
        }
#pragma unroll
        for (int k = 0; k < 2; k++) {
            const int j = j0 + k;
            const uint32_t sc[4] = {sv[k].x, sv[k].y, sv[k].z, sv[k].w};
            const uint32_t zz[4] = {zv[k].x, zv[k].y, zv[k].z, zv[k].w};
            uint32_t w0[4], w1[4];
#pragma unroll
            for (int i = 0; i < 4; i++) {
                w0[i] = tagf(p[j][i] * i0 * bf_lo(sc[i]), tag);
                w1[i] = tagf(p[j][i] * i1 * bf_hi(sc[i]), tag);
                c0 = fmaf(__uint_as_float(w0[i]), bf_lo(zz[i]), c0);
                c1 = fmaf(__uint_as_float(w1[i]), bf_hi(zz[i]), c1);
            }
            st_rlx16(wp + j * (2 * NT), w0[0], w0[1], w0[2], w0[3]);
            st_rlx16(wp + j * (2 * NT) + 1, w1[0], w1[1], w1[2], w1[3]);
        }
    }
    c0 = block_sum(c0, sm + 4 * NW);
    c1 = block_sum(c1, sm + 5 * NW);
    if (t == 0) {
        st_rlx8(P.scr->corr + h * 2, tagf(c0, tag), ((e0 - 20u) << 23) | tag);
        st_rlx8(P.scr->corr + h * 2 + 1, tagf(c1, tag), ((e1 - 20u) << 23) | tag);
    }
}

__device__ __forceinline__ void v_role(const Params& P, uint32_t v, float* sm) {
    const int t = threadIdx.x, w = t >> 5, lane = t & 31;
    const uint32_t h = v / EARLY, j = v % EARLY;
    const uint32_t row = h * S + (j * NW + w) * U;
    int4 vv[U];
    const int4* src = P.qv + (row * 32 + lane);
#pragma unroll
    for (int u = 0; u < U; u++) vv[u] = ld_stream(src + u * 32);
    const float4* wp = P.scr->wts + (row / 2 + (lane >> 4));
    uint4 wt = ld_rlx16(wp);
    const uint32_t tag = tag_of(ld_cnt(P));
    for (int it = 0; bad4(wt, tag) & 3u; it++) {
        if (it > SPIN_LIMIT) __trap();
        __nanosleep(100);
        wt = ld_rlx16(wp);
    }
    const float wu[4] = {__uint_as_float(wt.x), __uint_as_float(wt.y), __uint_as_float(wt.z), __uint_as_float(wt.w)};
    float o0 = (float)vv[0].x * wu[0], o1 = (float)vv[0].y * wu[0], o2 = (float)vv[0].z * wu[0], o3 = (float)vv[0].w * wu[0];
#pragma unroll
    for (int u = 1; u < U; u++) {
        o0 = fmaf((float)vv[u].x, wu[u], o0);
        o1 = fmaf((float)vv[u].y, wu[u], o1);
        o2 = fmaf((float)vv[u].z, wu[u], o2);
        o3 = fmaf((float)vv[u].w, wu[u], o3);
    }
    *(float4*)(sm + w * D + lane * 4) = make_float4(o0, o1, o2, o3);
    __syncthreads();
    if (t < D) {
        float r[NW];
#pragma unroll
        for (int k = 0; k < NW; k++) r[k] = sm[k * D + t];
        const float o = ((r[0] + r[1]) + (r[2] + r[3])) + ((r[4] + r[5]) + (r[6] + r[7]));
        const unsigned long long a = ((unsigned long long)__float2ll_rn(o) << CB) + 1ull;
        asm volatile("red.relaxed.gpu.global.add.u64 [%0], %1;" :: "l"(acc_ptr(P, h * NC + j % NC, t)), "l"(a) : "memory");
    }
}

__device__ __forceinline__ void f_role(const Params& P, uint32_t f, float* sm) {
    const int t = threadIdx.x, w = t >> 5, lane = t & 31;
    const uint32_t h = f / (D / FC), c = f % (D / FC), g = c * FC / 64;
    if (w == NW - 1) {
        const float2* cp = P.scr->corr + (h * 2 + g);
        const unsigned long long* ap = acc_ptr(P, h * NC, c * FC + (lane & (FC - 1)));
        const uint32_t tag = tag_of(ld_cnt(P));
        uint2 cu;
        unsigned long long ac[NC];
        for (int it = 0;; it++) {
            cu = ld_rlx8(cp);
#pragma unroll
            for (int k = 0; k < NC; k++) ac[k] = ld_rlx64(ap + k * (D / 16) * AS);
            uint32_t bad = ((cu.x ^ tag) | (cu.y ^ tag)) & 3u;
#pragma unroll
            for (int k = 0; k < NC; k++) bad |= ((uint32_t)ac[k] ^ (tag << 8 | (EARLY + NC - 1 - k) / NC)) & ((1u << CB) - 1u);
            if (!__any_sync(0xffffffffu, bad)) break;
            if (it > SPIN_LIMIT) __trap();
        }
        long long sum = 0;
#pragma unroll
        for (int k = 0; k < NC; k++) sum += (long long)ac[k] >> CB;
        const float scale = __uint_as_float(cu.y & ~3u);
        __nv_bfloat16* op = P.out + (h * D + c * FC + lane);
        sm[t] = __ll2float_rn(sum) - __uint_as_float(cu.x);
        asm volatile("bar.sync 1, 256;\nred.relaxed.gpu.global.add.u32 [%0], 1;" :: "l"(P.scr->cnt + lane) : "memory");
        float r[NW];
#pragma unroll
        for (int k = 0; k < NW; k++) r[k] = sm[k * 32 + lane];
        const float x = ((r[0] + r[1]) + (r[2] + r[3])) + ((r[4] + r[5]) + (r[6] + r[7]));
        if (lane < FC) *op = __float2bfloat16(x * scale);
        return;
    }
    const uint32_t row = h * S + (S - FR) + (w * (32 / LPR) + lane / LPR) * FU;
    const int4* src = P.qv + (row * 32 + c * LPR + lane % LPR);
    const float4* wp = P.scr->wts + (row / 2 + g);
    float o0 = 0.f, o1 = 0.f, o2 = 0.f, o3 = 0.f;
#pragma unroll 1
    for (int b = 0; b < NBT; b++) {
        int4 vv[FU];
        uint4 wt[FU / 4];
#pragma unroll
        for (int u = 0; u < FU; u++) vv[u] = ld_stream(src + (b * FB + u) * 32);
#pragma unroll
        for (int k = 0; k < FU / 4; k++) wt[k] = ld_rlx16(wp + (b * FB / 2 + 2 * k));
        const uint32_t tag = tag_of(ld_cnt(P));
        for (int it = 0;; it++) {
            uint32_t bad = 0;
#pragma unroll
            for (int k = 0; k < FU / 4; k++) bad |= bad4(wt[k], tag);
            if (!(bad & 3u)) break;
            if (it > SPIN_LIMIT) __trap();
            __nanosleep(100);
#pragma unroll
            for (int k = 0; k < FU / 4; k++) wt[k] = ld_rlx16(wp + (b * FB / 2 + 2 * k));
        }
#pragma unroll
        for (int u = 0; u < FU; u++) {
            const uint4 q = wt[u / 4];
            const float wu = __uint_as_float(u % 4 == 0 ? q.x : u % 4 == 1 ? q.y : u % 4 == 2 ? q.z : q.w);
            o0 = fmaf((float)vv[u].x, wu, o0);
            o1 = fmaf((float)vv[u].y, wu, o1);
            o2 = fmaf((float)vv[u].z, wu, o2);
            o3 = fmaf((float)vv[u].w, wu, o3);
        }
    }
    const bool up = (lane & 16) != 0, up2 = (lane & 8) != 0;
    const float a = (up ? o2 : o0) + __shfl_xor_sync(0xffffffffu, up ? o0 : o2, 16);
    const float b = (up ? o3 : o1) + __shfl_xor_sync(0xffffffffu, up ? o1 : o3, 16);
    const float o = (up2 ? b : a) + __shfl_xor_sync(0xffffffffu, up2 ? a : b, 8);
    sm[w * 32 + (lane & 7) * 4 + (lane >> 3)] = o;
    asm volatile("bar.arrive 1, 256;" ::: "memory");
}

__global__ void __launch_bounds__(NT, 4) attn_kernel(const Params P) {
    __shared__ __align__(16) float sm[NW * D];
    const uint32_t x = blockIdx.x, y = blockIdx.y;
    if (x >= SEG) {
        const int h = (int)y - (NW + SD);
        if (h >= 0 && h < H) s_role(P, h, sm);
        return;
    }
    if (y >= H) {
        const uint32_t v = (y - H) * SEG + x;
        if (v < H * EARLY) v_role(P, v, sm);
        else if (v < H * EARLY + NF) f_role(P, v - H * EARLY, sm);
        return;
    }
    k_role(P, x, y);
}

}

extern "C" void kernel_launch(void* const* d_in, const int* in_sizes, int n_in, void* d_out, int out_size) {
    (void)in_sizes; (void)n_in; (void)out_size;
    Params P;
    P.q = (const __nv_bfloat16*)d_in[0];
    P.qk = (const int4*)d_in[1];
    P.ks = (const __nv_bfloat16*)d_in[2];
    P.kz = (const __nv_bfloat16*)d_in[3];
    P.qv = (const int4*)d_in[4];
    P.vs = (const __nv_bfloat16*)d_in[5];
    P.vz = (const __nv_bfloat16*)d_in[6];
    P.qcos = (const __nv_bfloat16*)d_in[7];
    P.qsin = (const __nv_bfloat16*)d_in[8];
    P.kcos = (const __nv_bfloat16*)d_in[9];
    P.ksin = (const __nv_bfloat16*)d_in[10];
    P.out = (__nv_bfloat16*)d_out;
    void* scr = nullptr;
    cudaGetSymbolAddress(&scr, g_scr);
    P.scr = (Scratch*)scr;
    attn_kernel<<<dim3(GX, GY), NT>>>(P);
}
```

```cpp
#include <cuda_runtime.h>
#include <cuda_bf16.h>
#include <stdint.h>

namespace {

constexpr int H = 32, S = 8192, D = 128;
constexpr int NW = 8;
constexpr int NT = NW * 32;
constexpr int U = 4;
constexpr int SEG = S / (NW * U);
constexpr int CL = 2;
constexpr int GX = SEG + CL;
constexpr int HP = 2;
constexpr int SD = 4;
constexpr int FC = 32;
constexpr int FU = 8;
constexpr int NBT = 2;
constexpr int NC = 4;
constexpr int AS = 528;
constexpr int LPR = FC / 4;
constexpr int FB = (NW - 1) * (32 / LPR) * FU;
constexpr int FR = FB * NBT;
constexpr int EARLY = SEG - FR / (NW * U);
constexpr int NF = H * (D / FC);
constexpr int GY = H + (H * EARLY + NF + SEG - 1) / SEG;
constexpr int CB = 10;
static_assert(FR % (NW * U) == 0 && EARLY / NC < 255 && H + HP + SD <= GY, "layout");
constexpr int SPIN_LIMIT = 1 << 22;

struct Scratch {
    unsigned cnt[256];
    float4 wts[H * (S / 4) * 2];
    float logits[H * S];
    unsigned long long acc[H * NC * (D / 16) * AS];
    float2 corr[H * 2];
};
__device__ __align__(1024) Scratch g_scr;

__device__ __forceinline__ int4 ld_stream(const int4* p) {
    int4 v;
    asm volatile("ld.global.nc.L1::no_allocate.v4.s32 {%0,%1,%2,%3}, [%4];"
                 : "=r"(v.x), "=r"(v.y), "=r"(v.z), "=r"(v.w) : "l"(p));
    return v;
}
__device__ __forceinline__ uint2 ld_nc8(const void* p) {
    uint2 v;
    asm volatile("ld.global.nc.v2.u32 {%0,%1}, [%2];" : "=r"(v.x), "=r"(v.y) : "l"(p));
    return v;
}
__device__ __forceinline__ uint4 ld_nc16(const void* p) {
    uint4 v;
    asm volatile("ld.global.nc.v4.u32 {%0,%1,%2,%3}, [%4];"
                 : "=r"(v.x), "=r"(v.y), "=r"(v.z), "=r"(v.w) : "l"(p));
    return v;
}
__device__ __forceinline__ uint4 ld_nc16_na(const void* p) {
    uint4 v;
    asm volatile("ld.global.nc.L1::no_allocate.v4.u32 {%0,%1,%2,%3}, [%4];"
                 : "=r"(v.x), "=r"(v.y), "=r"(v.z), "=r"(v.w) : "l"(p));
    return v;
}
__device__ __forceinline__ uint2 ld_rlx8(const void* p) {
    uint2 v;
    asm volatile("ld.relaxed.gpu.global.v2.u32 {%0,%1}, [%2];" : "=r"(v.x), "=r"(v.y) : "l"(p) : "memory");
    return v;
}
__device__ __forceinline__ uint4 ld_rlx16(const void* p) {
    uint4 v;
    asm volatile("ld.relaxed.gpu.global.v4.u32 {%0,%1,%2,%3}, [%4];"
                 : "=r"(v.x), "=r"(v.y), "=r"(v.z), "=r"(v.w) : "l"(p) : "memory");
    return v;
}
__device__ __forceinline__ unsigned long long ld_rlx64(const void* p) {
    unsigned long long v;
    asm volatile("ld.relaxed.gpu.global.u64 %0, [%1];" : "=l"(v) : "l"(p) : "memory");
    return v;
}
__device__ __forceinline__ void st_rlx64(void* p, unsigned long long v) {
    asm volatile("st.relaxed.gpu.global.u64 [%0], %1;" :: "l"(p), "l"(v) : "memory");
}
__device__ __forceinline__ void st_rlx8(void* p, uint32_t a, uint32_t b) {
    asm volatile("st.relaxed.gpu.global.v2.u32 [%0], {%1,%2};" :: "l"(p), "r"(a), "r"(b) : "memory");
}
__device__ __forceinline__ void st_rlx16(void* p, uint32_t a, uint32_t b, uint32_t c, uint32_t d) {
    asm volatile("st.relaxed.gpu.global.v4.u32 [%0], {%1,%2,%3,%4};" :: "l"(p), "r"(a), "r"(b), "r"(c), "r"(d) : "memory");
}
__device__ __forceinline__ uint32_t bad4(const uint4& v, uint32_t tag) {
    return (v.x ^ tag) | (v.y ^ tag) | (v.z ^ tag) | (v.w ^ tag);
}
__device__ __forceinline__ uint32_t tagf(float x, uint32_t tag) { return (__float_as_uint(x) & ~3u) | tag; }
__device__ __forceinline__ float bf_lo(uint32_t x) { return __uint_as_float(x << 16); }
__device__ __forceinline__ float bf_hi(uint32_t x) { return __uint_as_float(x & 0xffff0000u); }
__device__ __forceinline__ float ex2(float x) { float y; asm("ex2.approx.ftz.f32 %0, %1;" : "=f"(y) : "f"(x)); return y; }
__device__ __forceinline__ uint32_t bf2_mul(uint32_t a, uint32_t b) {
    uint32_t r; asm("mul.rn.bf16x2 %0, %1, %2;" : "=r"(r) : "r"(a), "r"(b)); return r;
}
__device__ __forceinline__ uint32_t bf2_add(uint32_t a, uint32_t b) {
    uint32_t r; asm("add.rn.bf16x2 %0, %1, %2;" : "=r"(r) : "r"(a), "r"(b)); return r;
}

struct Params {
    const int4* qk;
    const int4* qv;
    Scratch* scr;
    const __nv_bfloat16* q;
    const __nv_bfloat16* qcos;
    const __nv_bfloat16* qsin;
    const __nv_bfloat16* kcos;
    const __nv_bfloat16* ksin;
    const __nv_bfloat16* ks;
    const __nv_bfloat16* kz;
    const __nv_bfloat16* vs;
    const __nv_bfloat16* vz;
    __nv_bfloat16* out;
};

__device__ __forceinline__ unsigned long long* acc_ptr(const Params& P, int hc, int col) {
    return P.scr->acc + (uint32_t)((hc * (D / 16) + (col >> 4)) * AS + (col & 15));
}
__device__ __forceinline__ uint32_t ld_cnt(const Params& P) {
    uint32_t c;
    asm volatile("ld.global.ca.u32 %0, [%1];" : "=r"(c) : "l"(P.scr->cnt));
    return c;
}
__device__ __forceinline__ uint32_t tag_of(uint32_t c) { return ((c / NF) + 1u) & 3u; }

#define SPLIT(p_) do { if ((p_) == nullptr) __trap(); } while (0)
__device__ __forceinline__ void k_role(const Params& P, uint32_t x, uint32_t y) {
    const uint32_t w = threadIdx.x >> 5, lane = threadIdx.x & 31;
    const uint32_t h = (y & ~(HP - 1u)) + w % HP, r0 = ((y % HP * SEG + x) * (NW / HP) + w / HP) * U;
    const uint32_t row = h * S + r0;
    const uint32_t cnt = ld_cnt(P);
    const uint2 qq = ld_nc8(P.q + (h * D + lane * 4));
    const uint2 qp = ld_nc8(P.q + (h * D + (lane ^ 16) * 4));
    const uint2 qc = ld_nc8(P.qcos + lane * 4);
    const uint2 qs = ld_nc8(P.qsin + lane * 4);
    int4 kv[U];
    const int4* src = P.qk + (row * 32 + lane);
    SPLIT(P.qk);
#pragma unroll
    for (int u = 0; u < U; u++) kv[u] = ld_stream(src + u * 32);
    SPLIT(P.kcos);
    uint2 cs[U], sn[U];
    const __nv_bfloat16* cp = P.kcos + (r0 * D + lane * 4);
    const __nv_bfloat16* sp = P.ksin + (r0 * D + (lane ^ 16) * 4);
#pragma unroll
    for (int u = 0; u < U; u++) {
        cs[u] = ld_nc8(cp + u * D);
        sn[u] = ld_nc8(sp + u * D);
    }
    const uint4 z4 = ld_nc16_na(P.kz + row * 2);
    const uint4 s4 = ld_nc16_na(P.ks + row * 2);
    const uint32_t zz[U] = {z4.x, z4.y, z4.z, z4.w}, sc[U] = {s4.x, s4.y, s4.z, s4.w};
    const uint32_t neg = (lane < 16) ? 0x80008000u : 0u;
    uint2 qr;
    qr.x = bf2_add(bf2_mul(qq.x, qc.x), bf2_mul(qp.x ^ neg, qs.x));
    qr.y = bf2_add(bf2_mul(qq.y, qc.y), bf2_mul(qp.y ^ neg, qs.y));
    uint2 qo;
    qo.x = __shfl_xor_sync(0xffffffffu, qr.x, 16);
    qo.y = __shfl_xor_sync(0xffffffffu, qr.y, 16);
    const float c = 0.08838834764831845f * 1.4426950408889634f;
    const float cb = (lane < 16) ? c : -c;
    const float qa0 = bf_lo(qr.x) * c, qa1 = bf_hi(qr.x) * c, qa2 = bf_lo(qr.y) * c, qa3 = bf_hi(qr.y) * c;
    const float qb0 = bf_lo(qo.x) * cb, qb1 = bf_hi(qo.x) * cb, qb2 = bf_lo(qo.y) * cb, qb3 = bf_hi(qo.y) * cb;
    const uint32_t sel = (lane < 16) ? 0x1044u : 0x3244u;

    float acc[U];
#pragma unroll
    for (int u = 0; u < U; u++) {
        const float z = __uint_as_float(__byte_perm(zz[u], 0u, sel));
        const float s = __uint_as_float(__byte_perm(sc[u], 0u, sel));
        const float a0 = fmaf(qa0, bf_lo(cs[u].x), qb0 * bf_lo(sn[u].x));
        const float a1 = fmaf(qa1, bf_hi(cs[u].x), qb1 * bf_hi(sn[u].x));
        const float a2 = fmaf(qa2, bf_lo(cs[u].y), qb2 * bf_lo(sn[u].y));
        const float a3 = fmaf(qa3, bf_hi(cs[u].y), qb3 * bf_hi(sn[u].y));
        float t = ((float)kv[u].x - z) * a0;
        t = fmaf((float)kv[u].y - z, a1, t);
        t = fmaf((float)kv[u].z - z, a2, t);
        t = fmaf((float)kv[u].w - z, a3, t);
        acc[u] = t * s;
    }
    const bool up = (lane & 16) != 0, up2 = (lane & 8) != 0;
    const float a = (up ? acc[2] : acc[0]) + __shfl_xor_sync(0xffffffffu, up ? acc[0] : acc[2], 16);
    const float b = (up ? acc[3] : acc[1]) + __shfl_xor_sync(0xffffffffu, up ? acc[1] : acc[3], 16);
    float lg = (up2 ? b : a) + __shfl_xor_sync(0xffffffffu, up2 ? a : b, 8);
#pragma unroll
    for (int off = 4; off > 0; off >>= 1) lg += __shfl_xor_sync(0xffffffffu, lg, off);
    asm volatile("{\n.reg .pred p;\nsetp.eq.u32 p, %2, 0;\n@p st.relaxed.gpu.global.u32 [%0], %1;\n}"
                 :: "l"(P.scr->logits + (row + (lane >> 3))), "r"(tagf(lg, tag_of(cnt))), "r"(lane & 7) : "memory");
}

__device__ __forceinline__ float block_sum(float x, float* s_red) {
#pragma unroll
    for (int o = 1; o < 32; o <<= 1) x += __shfl_xor_sync(0xffffffffu, x, o);
    if ((threadIdx.x & 31) == 0) s_red[threadIdx.x >> 5] = x;
    __syncthreads();
    const float4 a = *(const float4*)(s_red), b = *(const float4*)(s_red + 4);
    return ((a.x + a.y) + (a.z + a.w)) + ((b.x + b.y) + (b.z + b.w));
}

__device__ __forceinline__ void s_role(const Params& P, int h, float* sm) {
    constexpr int NB = S / (4 * NT);
    const int t = threadIdx.x;
    const uint32_t tag = tag_of(ld_cnt(P));
#pragma unroll
    for (int i = 0; i < (NC * D + NT - 1) / NT; i++)
        if (t + i * NT < NC * D) st_rlx64(acc_ptr(P, h * NC + (t + i * NT) / D, t % D), tag << 8);
    __threadfence();
    const float* lp = P.scr->logits + (h * S + t * 4);
    uint4 lg[NB];
    for (int it = 0;; it++) {
        uint32_t bad = 0;
#pragma unroll
        for (int j = 0; j < NB; j++) lg[j] = ld_rlx16(lp + j * (4 * NT));
#pragma unroll
        for (int j = 0; j < NB; j++) bad |= bad4(lg[j], tag);
        if (!__any_sync(0xffffffffu, bad & 3u)) break;
        if (it > SPIN_LIMIT) __trap();
        __nanosleep(500);
    }
    float m = __uint_as_float(lg[0].x);
#pragma unroll
    for (int j = 0; j < NB; j++)
        m = fmaxf(fmaxf(m, fmaxf(__uint_as_float(lg[j].x), __uint_as_float(lg[j].y))),
                  fmaxf(__uint_as_float(lg[j].z), __uint_as_float(lg[j].w)));
#pragma unroll
    for (int o = 1; o < 32; o <<= 1) m = fmaxf(m, __shfl_xor_sync(0xffffffffu, m, o));
    if ((t & 31) == 0) sm[t >> 5] = m;
    __syncthreads();
    {
        const float4 a = *(const float4*)(sm), b = *(const float4*)(sm + 4);
        m = fmaxf(fmaxf(fmaxf(a.x, a.y), fmaxf(a.z, a.w)), fmaxf(fmaxf(b.x, b.y), fmaxf(b.z, b.w)));
    }
    float p[NB][4];
    float l = 0.f;
#pragma unroll
    for (int j = 0; j < NB; j++) {
        p[j][0] = ex2(__uint_as_float(lg[j].x) - m);
        p[j][1] = ex2(__uint_as_float(lg[j].y) - m);
        p[j][2] = ex2(__uint_as_float(lg[j].z) - m);
        p[j][3] = ex2(__uint_as_float(lg[j].w) - m);
        l += (p[j][0] + p[j][1]) + (p[j][2] + p[j][3]);
    }
    const float inv = 1.f / block_sum(l, sm + NW);
    const __nv_bfloat16* vsp = P.vs + (h * S + t * 4) * 2;
    const __nv_bfloat16* vzp = P.vz + (h * S + t * 4) * 2;
    float a0 = 0.f, a1 = 0.f;
#pragma unroll
    for (int j0 = 0; j0 < NB; j0 += 4) {
        uint4 sv[4];
#pragma unroll
        for (int k = 0; k < 4; k++) sv[k] = ld_nc16(vsp + (j0 + k) * (8 * NT));
#pragma unroll
        for (int k = 0; k < 4; k++) {
            const uint32_t sc[4] = {sv[k].x, sv[k].y, sv[k].z, sv[k].w};
#pragma unroll
            for (int i = 0; i < 4; i++) {
                a0 = fmaf(p[j0 + k][i], fabsf(bf_lo(sc[i])), a0);
                a1 = fmaf(p[j0 + k][i], fabsf(bf_hi(sc[i])), a1);
            }
        }
    }
    const uint32_t e0 = min(max(__float_as_uint(block_sum(a0 * inv, sm + 2 * NW)) >> 23, 22u), 254u);
    const uint32_t e1 = min(max(__float_as_uint(block_sum(a1 * inv, sm + 3 * NW)) >> 23, 22u), 254u);
    const float i0 = inv * __uint_as_float((274u - e0) << 23), i1 = inv * __uint_as_float((274u - e1) << 23);
    float c0 = 0.f, c1 = 0.f;
    float4* wp = P.scr->wts + (h * (S / 4) + t) * 2;
#pragma unroll
    for (int j0 = 0; j0 < NB; j0 += 2) {
        uint4 sv[2], zv[2];
#pragma unroll
        for (int k = 0; k < 2; k++) {
            sv[k] = ld_nc16(vsp + (j0 + k) * (8 * NT));
            zv[k] = ld_nc16_na(vzp + (j0 + k) * (8 * NT));
        }
#pragma unroll
        for (int k = 0; k < 2; k++) {
            const int j = j0 + k;
            const uint32_t sc[4] = {sv[k].x, sv[k].y, sv[k].z, sv[k].w};
            const uint32_t zz[4] = {zv[k].x, zv[k].y, zv[k].z, zv[k].w};
            uint32_t w0[4], w1[4];
#pragma unroll
            for (int i = 0; i < 4; i++) {
                w0[i] = tagf(p[j][i] * i0 * bf_lo(sc[i]), tag);
                w1[i] = tagf(p[j][i] * i1 * bf_hi(sc[i]), tag);
                c0 = fmaf(__uint_as_float(w0[i]), bf_lo(zz[i]), c0);
                c1 = fmaf(__uint_as_float(w1[i]), bf_hi(zz[i]), c1);
            }
            st_rlx16(wp + j * (2 * NT), w0[0], w0[1], w0[2], w0[3]);
            st_rlx16(wp + j * (2 * NT) + 1, w1[0], w1[1], w1[2], w1[3]);
        }
    }
    c0 = block_sum(c0, sm + 4 * NW);
    c1 = block_sum(c1, sm + 5 * NW);
    if (t == 0) {
        st_rlx8(P.scr->corr + h * 2, tagf(c0, tag), ((e0 - 20u) << 23) | tag);
        st_rlx8(P.scr->corr + h * 2 + 1, tagf(c1, tag), ((e1 - 20u) << 23) | tag);
    }
}

__device__ __forceinline__ void v_role(const Params& P, uint32_t v, float* sm) {
    const int t = threadIdx.x, w = t >> 5, lane = t & 31;
    const uint32_t h = v / EARLY, j = v % EARLY;
    const uint32_t row = h * S + (j * NW + w) * U;
    int4 vv[U];
    const int4* src = P.qv + (row * 32 + lane);
#pragma unroll
    for (int u = 0; u < U; u++) vv[u] = ld_stream(src + u * 32);
    const float4* wp = P.scr->wts + (row / 2 + (lane >> 4));
    uint4 wt = ld_rlx16(wp);
    const uint32_t tag = tag_of(ld_cnt(P));
    for (int it = 0; bad4(wt, tag) & 3u; it++) {
        if (it > SPIN_LIMIT) __trap();
        __nanosleep(100);
        wt = ld_rlx16(wp);
    }
    const float wu[4] = {__uint_as_float(wt.x), __uint_as_float(wt.y), __uint_as_float(wt.z), __uint_as_float(wt.w)};
    float o0 = (float)vv[0].x * wu[0], o1 = (float)vv[0].y * wu[0], o2 = (float)vv[0].z * wu[0], o3 = (float)vv[0].w * wu[0];
#pragma unroll
    for (int u = 1; u < U; u++) {
        o0 = fmaf((float)vv[u].x, wu[u], o0);
        o1 = fmaf((float)vv[u].y, wu[u], o1);
        o2 = fmaf((float)vv[u].z, wu[u], o2);
        o3 = fmaf((float)vv[u].w, wu[u], o3);
    }
    *(float4*)(sm + w * D + lane * 4) = make_float4(o0, o1, o2, o3);
    __syncthreads();
    if (t < D) {
        float r[NW];
#pragma unroll
        for (int k = 0; k < NW; k++) r[k] = sm[k * D + t];
        const float o = ((r[0] + r[1]) + (r[2] + r[3])) + ((r[4] + r[5]) + (r[6] + r[7]));
        const unsigned long long a = ((unsigned long long)__float2ll_rn(o) << CB) + 1ull;
        asm volatile("red.relaxed.gpu.global.add.u64 [%0], %1;" :: "l"(acc_ptr(P, h * NC + j % NC, t)), "l"(a) : "memory");
    }
}

__device__ __forceinline__ void f_role(const Params& P, uint32_t f, float* sm) {
    const int t = threadIdx.x, w = t >> 5, lane = t & 31;
    const uint32_t h = f / (D / FC), c = f % (D / FC), g = c * FC / 64;
    if (w == NW - 1) {
        const float2* cp = P.scr->corr + (h * 2 + g);
        const unsigned long long* ap = acc_ptr(P, h * NC, c * FC + (lane & (FC - 1)));
        const uint32_t tag = tag_of(ld_cnt(P));
        uint2 cu;
        unsigned long long ac[NC];
        for (int it = 0;; it++) {
            cu = ld_rlx8(cp);
#pragma unroll
            for (int k = 0; k < NC; k++) ac[k] = ld_rlx64(ap + k * (D / 16) * AS);
            uint32_t bad = ((cu.x ^ tag) | (cu.y ^ tag)) & 3u;
#pragma unroll
            for (int k = 0; k < NC; k++) bad |= ((uint32_t)ac[k] ^ (tag << 8 | (EARLY + NC - 1 - k) / NC)) & ((1u << CB) - 1u);
            if (!__any_sync(0xffffffffu, bad)) break;
            if (it > SPIN_LIMIT) __trap();
        }
        long long sum = 0;
#pragma unroll
        for (int k = 0; k < NC; k++) sum += (long long)ac[k] >> CB;
        const float scale = __uint_as_float(cu.y & ~3u);
        __nv_bfloat16* op = P.out + (h * D + c * FC + lane);
        sm[t] = __ll2float_rn(sum) - __uint_as_float(cu.x);
        asm volatile("bar.sync 1, 256;\nred.relaxed.gpu.global.add.u32 [%0], 1;" :: "l"(P.scr->cnt + lane) : "memory");
        float r[NW];
#pragma unroll
        for (int k = 0; k < NW; k++) r[k] = sm[k * 32 + lane];
        const float x = ((r[0] + r[1]) + (r[2] + r[3])) + ((r[4] + r[5]) + (r[6] + r[7]));
        if (lane < FC) *op = __float2bfloat16(x * scale);
        return;
    }
    const uint32_t row = h * S + (S - FR) + (w * (32 / LPR) + lane / LPR) * FU;
    const int4* src = P.qv + (row * 32 + c * LPR + lane % LPR);
    const float4* wp = P.scr->wts + (row / 2 + g);
    float o0 = 0.f, o1 = 0.f, o2 = 0.f, o3 = 0.f;
#pragma unroll 1
    for (int b = 0; b < NBT; b++) {
        int4 vv[FU];
        uint4 wt[FU / 4];
#pragma unroll
        for (int u = 0; u < FU; u++) vv[u] = ld_stream(src + (b * FB + u) * 32);
#pragma unroll
        for (int k = 0; k < FU / 4; k++) wt[k] = ld_rlx16(wp + (b * FB / 2 + 2 * k));
        const uint32_t tag = tag_of(ld_cnt(P));
        for (int it = 0;; it++) {
            uint32_t bad = 0;
#pragma unroll
            for (int k = 0; k < FU / 4; k++) bad |= bad4(wt[k], tag);
            if (!(bad & 3u)) break;
            if (it > SPIN_LIMIT) __trap();
            __nanosleep(100);
#pragma unroll
            for (int k = 0; k < FU / 4; k++) wt[k] = ld_rlx16(wp + (b * FB / 2 + 2 * k));
        }
#pragma unroll
        for (int u = 0; u < FU; u++) {
            const uint4 q = wt[u / 4];
            const float wu = __uint_as_float(u % 4 == 0 ? q.x : u % 4 == 1 ? q.y : u % 4 == 2 ? q.z : q.w);
            o0 = fmaf((float)vv[u].x, wu, o0);
            o1 = fmaf((float)vv[u].y, wu, o1);
            o2 = fmaf((float)vv[u].z, wu, o2);
            o3 = fmaf((float)vv[u].w, wu, o3);
        }
    }
    const bool up = (lane & 16) != 0, up2 = (lane & 8) != 0;
    const float a = (up ? o2 : o0) + __shfl_xor_sync(0xffffffffu, up ? o0 : o2, 16);
    const float b = (up ? o3 : o1) + __shfl_xor_sync(0xffffffffu, up ? o1 : o3, 16);
    const float o = (up2 ? b : a) + __shfl_xor_sync(0xffffffffu, up2 ? a : b, 8);
    sm[w * 32 + (lane & 7) * 4 + (lane >> 3)] = o;
    asm volatile("bar.arrive 1, 256;" ::: "memory");
}

__global__ void __cluster_dims__(CL, 1, 1) __launch_bounds__(NT, 4) attn_kernel(const Params P) {
    __shared__ __align__(16) float sm[NW * D];
    const uint32_t x = blockIdx.x, y = blockIdx.y;
    if (x >= SEG) {
        const int h = (int)y - (HP + SD);
        if (x == SEG && h >= 0 && h < H) s_role(P, h, sm);
        return;
    }
    if (y >= H) {
        const uint32_t v = (y - H) * SEG + x;
        if (v < H * EARLY) v_role(P, v, sm);
        else if (v < H * EARLY + NF) f_role(P, v - H * EARLY, sm);
        return;
    }
    k_role(P, x, y);
}

}

extern "C" void kernel_launch(void* const* d_in, const int* in_sizes, int n_in, void* d_out, int out_size) {
    (void)in_sizes; (void)n_in; (void)out_size;
    Params P;
    P.q = (const __nv_bfloat16*)d_in[0];
    P.qk = (const int4*)d_in[1];
    P.ks = (const __nv_bfloat16*)d_in[2];
    P.kz = (const __nv_bfloat16*)d_in[3];
    P.qv = (const int4*)d_in[4];
    P.vs = (const __nv_bfloat16*)d_in[5];
    P.vz = (const __nv_bfloat16*)d_in[6];
    P.qcos = (const __nv_bfloat16*)d_in[7];
    P.qsin = (const __nv_bfloat16*)d_in[8];
    P.kcos = (const __nv_bfloat16*)d_in[9];
    P.ksin = (const __nv_bfloat16*)d_in[10];
    P.out = (__nv_bfloat16*)d_out;
    void* scr = nullptr;
    cudaGetSymbolAddress(&scr, g_scr);
    P.scr = (Scratch*)scr;
    attn_kernel<<<dim3(GX, GY), NT>>>(P);
}
```

```cpp
#include <cuda_runtime.h>
#include <cuda_bf16.h>
#include <stdint.h>

namespace {

constexpr int H = 32, S = 8192, D = 128;
constexpr int NW = 8;
constexpr int NT = NW * 32;
constexpr int U = 4;
constexpr int SEG = S / (NW * U);
constexpr int CL = 2;
constexpr int GX = SEG + CL;
constexpr int HP = 2;
constexpr int SD = 4;
constexpr int PD = 3;
constexpr int FC = 16;
constexpr int NC = 32 / FC;
constexpr int AS = 528;
constexpr int LPR = FC / 4;
constexpr int FR = (NW - 1) * (32 / LPR) * U;
constexpr int EARLY = SEG - FR / (NW * U);
constexpr int NF = H * (D / FC);
constexpr int GY = H + (H * EARLY + NF + SEG - 1) / SEG;
constexpr int CB = 10;
static_assert(FR % (NW * U) == 0 && (H - 1) * (SEG / H) <= EARLY && EARLY / NC < 255 && H + HP + SD <= GY && FC == 16 && CL == 2, "layout");
constexpr int SPIN_LIMIT = 1 << 22;

struct Scratch {
    unsigned cnt[256];
    float4 wts[H * (S / 4) * 2];
    float logits[H * S];
    unsigned long long acc[H * NC * (D / 16) * AS];
    float2 corr[H * 2];
};
__device__ __align__(1024) Scratch g_scr;

__device__ __forceinline__ int4 ld_stream(const int4* p) {
    int4 v;
    asm volatile("ld.global.nc.L1::no_allocate.v4.s32 {%0,%1,%2,%3}, [%4];"
                 : "=r"(v.x), "=r"(v.y), "=r"(v.z), "=r"(v.w) : "l"(p));
    return v;
}
__device__ __forceinline__ int4 ld_half(const int4* p) {
    int4 v;
    asm volatile("ld.global.nc.L1::no_allocate.L2::128B.v4.s32 {%0,%1,%2,%3}, [%4];"
                 : "=r"(v.x), "=r"(v.y), "=r"(v.z), "=r"(v.w) : "l"(p));
    return v;
}
__device__ __forceinline__ uint2 ld_nc8(const void* p) {
    uint2 v;
    asm volatile("ld.global.nc.v2.u32 {%0,%1}, [%2];" : "=r"(v.x), "=r"(v.y) : "l"(p));
    return v;
}
__device__ __forceinline__ uint4 ld_nc16(const void* p) {
    uint4 v;
    asm volatile("ld.global.nc.v4.u32 {%0,%1,%2,%3}, [%4];"
                 : "=r"(v.x), "=r"(v.y), "=r"(v.z), "=r"(v.w) : "l"(p));
    return v;
}
__device__ __forceinline__ uint4 ld_nc16_na(const void* p) {
    uint4 v;
    asm volatile("ld.global.nc.L1::no_allocate.v4.u32 {%0,%1,%2,%3}, [%4];"
                 : "=r"(v.x), "=r"(v.y), "=r"(v.z), "=r"(v.w) : "l"(p));
    return v;
}
__device__ __forceinline__ uint2 ld_rlx8(const void* p) {
    uint2 v;
    asm volatile("ld.relaxed.gpu.global.v2.u32 {%0,%1}, [%2];" : "=r"(v.x), "=r"(v.y) : "l"(p) : "memory");
    return v;
}
__device__ __forceinline__ uint4 ld_rlx16(const void* p) {
    uint4 v;
    asm volatile("ld.relaxed.gpu.global.v4.u32 {%0,%1,%2,%3}, [%4];"
                 : "=r"(v.x), "=r"(v.y), "=r"(v.z), "=r"(v.w) : "l"(p) : "memory");
    return v;
}
__device__ __forceinline__ unsigned long long ld_rlx64(const void* p) {
    unsigned long long v;
    asm volatile("ld.relaxed.gpu.global.u64 %0, [%1];" : "=l"(v) : "l"(p) : "memory");
    return v;
}
__device__ __forceinline__ void st_rlx64(void* p, unsigned long long v) {
    asm volatile("st.relaxed.gpu.global.u64 [%0], %1;" :: "l"(p), "l"(v) : "memory");
}
__device__ __forceinline__ void st_rlx8(void* p, uint32_t a, uint32_t b) {
    asm volatile("st.relaxed.gpu.global.v2.u32 [%0], {%1,%2};" :: "l"(p), "r"(a), "r"(b) : "memory");
}
__device__ __forceinline__ void st_rlx16(void* p, uint32_t a, uint32_t b, uint32_t c, uint32_t d) {
    asm volatile("st.relaxed.gpu.global.v4.u32 [%0], {%1,%2,%3,%4};" :: "l"(p), "r"(a), "r"(b), "r"(c), "r"(d) : "memory");
}
__device__ __forceinline__ uint32_t bad4(const uint4& v, uint32_t tag) {
    return (v.x ^ tag) | (v.y ^ tag) | (v.z ^ tag) | (v.w ^ tag);
}
__device__ __forceinline__ uint32_t tagf(float x, uint32_t tag) { return (__float_as_uint(x) & ~3u) | tag; }
__device__ __forceinline__ float bf_lo(uint32_t x) { return __uint_as_float(x << 16); }
__device__ __forceinline__ float bf_hi(uint32_t x) { return __uint_as_float(x & 0xffff0000u); }
__device__ __forceinline__ float ex2(float x) { float y; asm("ex2.approx.ftz.f32 %0, %1;" : "=f"(y) : "f"(x)); return y; }
__device__ __forceinline__ uint32_t bf2_mul(uint32_t a, uint32_t b) {
    uint32_t r; asm("mul.rn.bf16x2 %0, %1, %2;" : "=r"(r) : "r"(a), "r"(b)); return r;
}
__device__ __forceinline__ uint32_t bf2_add(uint32_t a, uint32_t b) {
    uint32_t r; asm("add.rn.bf16x2 %0, %1, %2;" : "=r"(r) : "r"(a), "r"(b)); return r;
}

struct Params {
    const int4* qk;
    const int4* qv;
    Scratch* scr;
    const __nv_bfloat16* q;
    const __nv_bfloat16* qcos;
    const __nv_bfloat16* qsin;
    const __nv_bfloat16* kcos;
    const __nv_bfloat16* ksin;
    const __nv_bfloat16* ks;
    const __nv_bfloat16* kz;
    const __nv_bfloat16* vs;
    const __nv_bfloat16* vz;
    __nv_bfloat16* out;
};

__device__ __forceinline__ unsigned long long* acc_ptr(const Params& P, int hc, int col) {
    return P.scr->acc + (uint32_t)((hc * (D / 16) + (col >> 4)) * AS + (col & 15));
}
__device__ __forceinline__ uint32_t ld_cnt(const Params& P) {
    uint32_t c;
    asm volatile("ld.global.ca.u32 %0, [%1];" : "=r"(c) : "l"(P.scr->cnt));
    return c;
}
__device__ __forceinline__ uint32_t tag_of(uint32_t c) { return ((c / NF) + 1u) & 3u; }
__device__ __forceinline__ uint32_t f_block(uint32_t h) { return (H - 1 - h) * (SEG / H); }

#define SPLIT(p_) do { if ((p_) == nullptr) __trap(); } while (0)
__device__ __forceinline__ void k_role(const Params& P, uint32_t x, uint32_t y) {
    const uint32_t w = threadIdx.x >> 5, lane = threadIdx.x & 31;
    const uint32_t h = (y & ~(HP - 1u)) + w % HP, r0 = ((y % HP * SEG + x) * (NW / HP) + w / HP) * U;
    const uint32_t row = h * S + r0;
    const uint32_t cnt = ld_cnt(P);
    const uint2 qq = ld_nc8(P.q + (h * D + lane * 4));
    const uint2 qp = ld_nc8(P.q + (h * D + (lane ^ 16) * 4));
    const uint2 qc = ld_nc8(P.qcos + lane * 4);
    const uint2 qs = ld_nc8(P.qsin + lane * 4);
    int4 kv[U];
    const int4* src = P.qk + (row * 32 + lane);
    SPLIT(P.qk);
#pragma unroll
    for (int u = 0; u < U; u++) kv[u] = ld_stream(src + u * 32);
    SPLIT(P.kcos);
    uint2 cs[U], sn[U];
    const __nv_bfloat16* cp = P.kcos + (r0 * D + lane * 4);
    const __nv_bfloat16* sp = P.ksin + (r0 * D + (lane ^ 16) * 4);
#pragma unroll
    for (int u = 0; u < U; u++) {
        cs[u] = ld_nc8(cp + u * D);
        sn[u] = ld_nc8(sp + u * D);
    }
    const uint4 z4 = ld_nc16_na(P.kz + row * 2);
    const uint4 s4 = ld_nc16_na(P.ks + row * 2);
    const uint32_t zz[U] = {z4.x, z4.y, z4.z, z4.w}, sc[U] = {s4.x, s4.y, s4.z, s4.w};
    const uint32_t neg = (lane < 16) ? 0x80008000u : 0u;
    uint2 qr;
    qr.x = bf2_add(bf2_mul(qq.x, qc.x), bf2_mul(qp.x ^ neg, qs.x));
    qr.y = bf2_add(bf2_mul(qq.y, qc.y), bf2_mul(qp.y ^ neg, qs.y));
    uint2 qo;
    qo.x = __shfl_xor_sync(0xffffffffu, qr.x, 16);
    qo.y = __shfl_xor_sync(0xffffffffu, qr.y, 16);
    const float c = 0.08838834764831845f * 1.4426950408889634f;
    const float cb = (lane < 16) ? c : -c;
    const float qa0 = bf_lo(qr.x) * c, qa1 = bf_hi(qr.x) * c, qa2 = bf_lo(qr.y) * c, qa3 = bf_hi(qr.y) * c;
    const float qb0 = bf_lo(qo.x) * cb, qb1 = bf_hi(qo.x) * cb, qb2 = bf_lo(qo.y) * cb, qb3 = bf_hi(qo.y) * cb;
    const uint32_t sel = (lane < 16) ? 0x1044u : 0x3244u;

    float acc[U];
#pragma unroll
    for (int u = 0; u < U; u++) {
        const float z = __uint_as_float(__byte_perm(zz[u], 0u, sel));
        const float s = __uint_as_float(__byte_perm(sc[u], 0u, sel));
        const float a0 = fmaf(qa0, bf_lo(cs[u].x), qb0 * bf_lo(sn[u].x));
        const float a1 = fmaf(qa1, bf_hi(cs[u].x), qb1 * bf_hi(sn[u].x));
        const float a2 = fmaf(qa2, bf_lo(cs[u].y), qb2 * bf_lo(sn[u].y));
        const float a3 = fmaf(qa3, bf_hi(cs[u].y), qb3 * bf_hi(sn[u].y));
        float t = ((float)kv[u].x - z) * a0;
        t = fmaf((float)kv[u].y - z, a1, t);
        t = fmaf((float)kv[u].z - z, a2, t);
        t = fmaf((float)kv[u].w - z, a3, t);
        acc[u] = t * s;
    }
    const bool up = (lane & 16) != 0, up2 = (lane & 8) != 0;
    const float a = (up ? acc[2] : acc[0]) + __shfl_xor_sync(0xffffffffu, up ? acc[0] : acc[2], 16);
    const float b = (up ? acc[3] : acc[1]) + __shfl_xor_sync(0xffffffffu, up ? acc[1] : acc[3], 16);
    float lg = (up2 ? b : a) + __shfl_xor_sync(0xffffffffu, up2 ? a : b, 8);
#pragma unroll
    for (int off = 4; off > 0; off >>= 1) lg += __shfl_xor_sync(0xffffffffu, lg, off);
    asm volatile("{\n.reg .pred p;\nsetp.eq.u32 p, %2, 0;\n@p st.relaxed.gpu.global.u32 [%0], %1;\n}"
                 :: "l"(P.scr->logits + (row + (lane >> 3))), "r"(tagf(lg, tag_of(cnt))), "r"(lane & 7) : "memory");
}

__device__ __forceinline__ float block_sum(float x, float* s_red) {
#pragma unroll
    for (int o = 1; o < 32; o <<= 1) x += __shfl_xor_sync(0xffffffffu, x, o);
    if ((threadIdx.x & 31) == 0) s_red[threadIdx.x >> 5] = x;
    __syncthreads();
    const float4 a = *(const float4*)(s_red), b = *(const float4*)(s_red + 4);
    return ((a.x + a.y) + (a.z + a.w)) + ((b.x + b.y) + (b.z + b.w));
}

__device__ __forceinline__ void s_role(const Params& P, int h, float* sm) {
    constexpr int NB = S / (4 * NT);
    const int t = threadIdx.x;
    const uint32_t tag = tag_of(ld_cnt(P));
#pragma unroll
    for (int i = 0; i < (NC * D + NT - 1) / NT; i++)
        if (t + i * NT < NC * D) st_rlx64(acc_ptr(P, h * NC + (t + i * NT) / D, t % D), tag << 8);
    __threadfence();
    const float* lp = P.scr->logits + (h * S + t * 4);
    uint4 lg[NB];
    for (int it = 0;; it++) {
        uint32_t bad = 0;
#pragma unroll
        for (int j = 0; j < NB; j++) lg[j] = ld_rlx16(lp + j * (4 * NT));
#pragma unroll
        for (int j = 0; j < NB; j++) bad |= bad4(lg[j], tag);
        if (!__any_sync(0xffffffffu, bad & 3u)) break;
        if (it > SPIN_LIMIT) break;
        __nanosleep(500);
    }
    float m = __uint_as_float(lg[0].x);
#pragma unroll
    for (int j = 0; j < NB; j++)
        m = fmaxf(fmaxf(m, fmaxf(__uint_as_float(lg[j].x), __uint_as_float(lg[j].y))),
                  fmaxf(__uint_as_float(lg[j].z), __uint_as_float(lg[j].w)));
#pragma unroll
    for (int o = 1; o < 32; o <<= 1) m = fmaxf(m, __shfl_xor_sync(0xffffffffu, m, o));
    if ((t & 31) == 0) sm[t >> 5] = m;
    __syncthreads();
    {
        const float4 a = *(const float4*)(sm), b = *(const float4*)(sm + 4);
        m = fmaxf(fmaxf(fmaxf(a.x, a.y), fmaxf(a.z, a.w)), fmaxf(fmaxf(b.x, b.y), fmaxf(b.z, b.w)));
    }
    float p[NB][4];
    float l = 0.f;
#pragma unroll
    for (int j = 0; j < NB; j++) {
        p[j][0] = ex2(__uint_as_float(lg[j].x) - m);
        p[j][1] = ex2(__uint_as_float(lg[j].y) - m);
        p[j][2] = ex2(__uint_as_float(lg[j].z) - m);
        p[j][3] = ex2(__uint_as_float(lg[j].w) - m);
        l += (p[j][0] + p[j][1]) + (p[j][2] + p[j][3]);
    }
    const float inv = 1.f / block_sum(l, sm + NW);
    const __nv_bfloat16* vsp = P.vs + (h * S + t * 4) * 2;
    const __nv_bfloat16* vzp = P.vz + (h * S + t * 4) * 2;
    float a0 = 0.f, a1 = 0.f;
#pragma unroll
    for (int j0 = 0; j0 < NB; j0 += 4) {
        uint4 sv[4];
#pragma unroll
        for (int k = 0; k < 4; k++) sv[k] = ld_nc16(vsp + (j0 + k) * (8 * NT));
#pragma unroll
        for (int k = 0; k < 4; k++) {
            const uint32_t sc[4] = {sv[k].x, sv[k].y, sv[k].z, sv[k].w};
#pragma unroll
            for (int i = 0; i < 4; i++) {
                a0 = fmaf(p[j0 + k][i], fabsf(bf_lo(sc[i])), a0);
                a1 = fmaf(p[j0 + k][i], fabsf(bf_hi(sc[i])), a1);
            }
        }
    }
    const uint32_t e0 = min(max(__float_as_uint(block_sum(a0 * inv, sm + 2 * NW)) >> 23, 22u), 254u);
    const uint32_t e1 = min(max(__float_as_uint(block_sum(a1 * inv, sm + 3 * NW)) >> 23, 22u), 254u);
    const float i0 = inv * __uint_as_float((274u - e0) << 23), i1 = inv * __uint_as_float((274u - e1) << 23);
    float c0 = 0.f, c1 = 0.f;
    float4* wp = P.scr->wts + (h * (S / 4) + t) * 2;
#pragma unroll
    for (int j0 = 0; j0 < NB; j0 += 2) {
        uint4 sv[2], zv[2];
#pragma unroll
        for (int k = 0; k < 2; k++) {
            sv[k] = ld_nc16(vsp + (j0 + k) * (8 * NT));
            zv[k] = ld_nc16_na(vzp + (j0 + k) * (8 * NT));
        }
#pragma unroll
        for (int k = 0; k < 2; k++) {
            const int j = j0 + k;
            const uint32_t sc[4] = {sv[k].x, sv[k].y, sv[k].z, sv[k].w};
            const uint32_t zz[4] = {zv[k].x, zv[k].y, zv[k].z, zv[k].w};
            uint32_t w0[4], w1[4];
#pragma unroll
            for (int i = 0; i < 4; i++) {
                w0[i] = tagf(p[j][i] * i0 * bf_lo(sc[i]), tag);
                w1[i] = tagf(p[j][i] * i1 * bf_hi(sc[i]), tag);
                c0 = fmaf(__uint_as_float(w0[i]), bf_lo(zz[i]), c0);
                c1 = fmaf(__uint_as_float(w1[i]), bf_hi(zz[i]), c1);
            }
            st_rlx16(wp + j * (2 * NT), w0[0], w0[1], w0[2], w0[3]);
            st_rlx16(wp + j * (2 * NT) + 1, w1[0], w1[1], w1[2], w1[3]);
        }
    }
    c0 = block_sum(c0, sm + 4 * NW);
    c1 = block_sum(c1, sm + 5 * NW);
    if (t == 0) {
        st_rlx8(P.scr->corr + h * 2, tagf(c0, tag), ((e0 - 20u) << 23) | tag);
        st_rlx8(P.scr->corr + h * 2 + 1, tagf(c1, tag), ((e1 - 20u) << 23) | tag);
    }
}

__device__ __forceinline__ void v_role(const Params& P, uint32_t v, float* sm) {
    const int t = threadIdx.x, w = t >> 5, lane = t & 31;
    const uint32_t h = v / EARLY, j = v % EARLY;
    const uint32_t row = h * S + ((j + (j >= f_block(h) ? SEG - EARLY : 0)) * NW + w) * U;
    int4 vv[U];
    const int4* src = P.qv + (row * 32 + lane);
#pragma unroll
    for (int u = 0; u < U; u++) vv[u] = ld_stream(src + u * 32);
    const float4* wp = P.scr->wts + (row / 2 + (lane >> 4));
    uint4 wt = ld_rlx16(wp);
    const uint32_t tag = tag_of(ld_cnt(P));
    for (int it = 0; bad4(wt, tag) & 3u; it++) {
        if (it > SPIN_LIMIT) break;
        __nanosleep(100);
        wt = ld_rlx16(wp);
    }
    const float wu[4] = {__uint_as_float(wt.x), __uint_as_float(wt.y), __uint_as_float(wt.z), __uint_as_float(wt.w)};
    float o0 = (float)vv[0].x * wu[0], o1 = (float)vv[0].y * wu[0], o2 = (float)vv[0].z * wu[0], o3 = (float)vv[0].w * wu[0];
#pragma unroll
    for (int u = 1; u < U; u++) {
        o0 = fmaf((float)vv[u].x, wu[u], o0);
        o1 = fmaf((float)vv[u].y, wu[u], o1);
        o2 = fmaf((float)vv[u].z, wu[u], o2);
        o3 = fmaf((float)vv[u].w, wu[u], o3);
    }
    *(float4*)(sm + w * D + lane * 4) = make_float4(o0, o1, o2, o3);
    __syncthreads();
    if (t < D) {
        float r[NW];
#pragma unroll
        for (int k = 0; k < NW; k++) r[k] = sm[k * D + t];
        const float o = ((r[0] + r[1]) + (r[2] + r[3])) + ((r[4] + r[5]) + (r[6] + r[7]));
        const unsigned long long a = ((unsigned long long)__float2ll_rn(o) << CB) + 1ull;
        asm volatile("red.relaxed.gpu.global.add.u64 [%0], %1;" :: "l"(acc_ptr(P, h * NC + j % NC, t)), "l"(a) : "memory");
    }
}

#define PIN32(x_) asm volatile("" : "+r"(x_))
#define PIN64(x_) asm volatile("" : "+l"(x_))
__device__ __forceinline__ void f_role(const Params& P, uint32_t f, float* sm) {
    const int t = threadIdx.x, w = t >> 5, lane = t & 31;
    const uint32_t h = f / (D / FC), c = f % (D / FC), g = c * FC / 64;
    uint32_t sb = (uint32_t)__cvta_generic_to_shared(sm);
    PIN32(sb);
    if (w == NW - 1) {
        const float2* cp = P.scr->corr + (h * 2 + g);
        const unsigned long long* ap = acc_ptr(P, h * NC + lane / FC, c * FC + lane % FC);
        unsigned long long ac = ld_rlx64(ap);
        uint2 cu = ld_rlx8(cp);
        const uint32_t tag = tag_of(ld_cnt(P));
        const uint32_t want = tag << 8 | (EARLY + NC - 1 - lane / FC) / NC;
        uint32_t sa = sb + lane * 4;
        __nv_bfloat16* op = P.out + (h * D + c * FC + lane);
        unsigned* cn = P.scr->cnt + lane;
        PIN32(sa); PIN64(op); PIN64(cn);
        for (int it = 0;; it++) {
            const uint32_t bc = ((cu.x ^ tag) | (cu.y ^ tag)) & 3u;
            if (!__any_sync(0xffffffffu, bc | (((uint32_t)ac ^ want) & ((1u << CB) - 1u)))) break;
            if (it > SPIN_LIMIT) break;
            ac = ld_rlx64(ap);
            if (bc) cu = ld_rlx8(cp);
        }
        const float scale = __uint_as_float(cu.y & ~3u);
        float r[NW];
        asm volatile("bar.sync 1, 256;" ::: "memory");
#pragma unroll
        for (int k = 0; k < NW - 1; k++) asm volatile("ld.shared.f32 %0, [%1];" : "=f"(r[k]) : "r"(sa + k * 128) : "memory");
        long long sum = (long long)ac >> CB;
        sum += __shfl_xor_sync(0xffffffffu, sum, 16);
        r[NW - 1] = __ll2float_rn(sum) - __uint_as_float(cu.x);
        const float x = ((r[0] + r[1]) + (r[2] + r[3])) + ((r[4] + r[5]) + (r[6] + r[7]));
        const __nv_bfloat16 ob = __float2bfloat16(x * scale);
        asm volatile("{\n.reg .pred p;\nsetp.lt.u32 p, %3, %4;\n@p st.global.u16 [%0], %1;\nred.relaxed.gpu.global.add.u32 [%2], 1;\n}"
                     :: "l"(op), "h"(__bfloat16_as_ushort(ob)), "l"(cn), "r"(lane), "n"(FC) : "memory");
        return;
    }
    const uint32_t row = h * S + f_block(h) * (NW * U) + (w * (32 / LPR) + lane / LPR) * U;
    const int4* src = P.qv + (row * 32 + c * LPR + lane % LPR);
    uint32_t sa = sb + (w * 32 + (lane & 7) * 4 + (lane >> 3)) * 4;
    const float4* wp = P.scr->wts + (row / 2 + g);
    int4 vv[U];
#pragma unroll
    for (int u = 0; u < U; u++) vv[u] = ld_half(src + u * 32);
    uint4 wt = ld_rlx16(wp);
    const uint32_t tag = tag_of(ld_cnt(P));
    PIN32(sa);
    for (int it = 0; bad4(wt, tag) & 3u; it++) {
        if (it > SPIN_LIMIT) break;
        __nanosleep(100);
        wt = ld_rlx16(wp);
    }
    __syncwarp();
    const float wu[4] = {__uint_as_float(wt.x), __uint_as_float(wt.y), __uint_as_float(wt.z), __uint_as_float(wt.w)};
    float o0 = (float)vv[0].x * wu[0], o1 = (float)vv[0].y * wu[0], o2 = (float)vv[0].z * wu[0], o3 = (float)vv[0].w * wu[0];
#pragma unroll
    for (int u = 1; u < U; u++) {
        o0 = fmaf((float)vv[u].x, wu[u], o0);
        o1 = fmaf((float)vv[u].y, wu[u], o1);
        o2 = fmaf((float)vv[u].z, wu[u], o2);
        o3 = fmaf((float)vv[u].w, wu[u], o3);
    }
    const bool up = (lane & 16) != 0, up2 = (lane & 8) != 0;
    const float a = (up ? o2 : o0) + __shfl_xor_sync(0xffffffffu, up ? o0 : o2, 16);
    const float b = (up ? o3 : o1) + __shfl_xor_sync(0xffffffffu, up ? o1 : o3, 16);
    float o = (up2 ? b : a) + __shfl_xor_sync(0xffffffffu, up2 ? a : b, 8);
    o += __shfl_xor_sync(0xffffffffu, o, 4);
    asm volatile("st.shared.f32 [%0], %1;\nbar.arrive 1, 256;" :: "r"(sa), "f"(o) : "memory");
}

__global__ void __cluster_dims__(CL, 1, 1) __launch_bounds__(NT, 4) attn_kernel(const Params P) {
    __shared__ __align__(16) float sm[NW * D];
    const uint32_t x = blockIdx.x, y = blockIdx.y;
    if (x >= SEG) {
        const int h = (int)y - (HP + SD);
        if (x == SEG + 1 && y + PD < H && threadIdx.x < 2 * HP) {
            const uint32_t yy = y + PD, i = threadIdx.x;
            const __nv_bfloat16* a = (i >= HP ? P.ks : P.kz) + (((yy & ~(HP - 1u)) + i % HP) * S + yy % HP * (S / HP)) * 2;
            asm volatile("cp.async.bulk.prefetch.L2.global [%0], %1;" :: "l"(a), "r"(S / HP * 4) : "memory");
        }
        if (x == SEG && h >= 0 && h < H) s_role(P, h, sm);
        return;
    }
    if (y >= H) {
        const uint32_t v = (y - H) * SEG + x;
        if (v < H * EARLY) v_role(P, v, sm);
        else if (v < H * EARLY + NF) f_role(P, v - H * EARLY, sm);
        return;
    }
    k_role(P, x, y);
}

}

extern "C" void kernel_launch(void* const* d_in, const int* in_sizes, int n_in, void* d_out, int out_size) {
    (void)in_sizes; (void)n_in; (void)out_size;
    Params P;
    P.q = (const __nv_bfloat16*)d_in[0];
    P.qk = (const int4*)d_in[1];
    P.ks = (const __nv_bfloat16*)d_in[2];
    P.kz = (const __nv_bfloat16*)d_in[3];
    P.qv = (const int4*)d_in[4];
    P.vs = (const __nv_bfloat16*)d_in[5];
    P.vz = (const __nv_bfloat16*)d_in[6];
    P.qcos = (const __nv_bfloat16*)d_in[7];
    P.qsin = (const __nv_bfloat16*)d_in[8];
    P.kcos = (const __nv_bfloat16*)d_in[9];
    P.ksin = (const __nv_bfloat16*)d_in[10];
    P.out = (__nv_bfloat16*)d_out;
    void* scr = nullptr;
    cudaGetSymbolAddress(&scr, g_scr);
    P.scr = (Scratch*)scr;
    attn_kernel<<<dim3(GX, GY), NT>>>(P);
}
```

```cpp
#include <cuda_runtime.h>
#include <cuda_bf16.h>
#include <stdint.h>

namespace {

constexpr int H = 32, S = 8192, D = 128;
constexpr int NW = 8;
constexpr int NT = NW * 32;
constexpr int U = 4;
constexpr int SEG = S / (NW * U);
constexpr int CL = 2;
constexpr int GX = SEG + CL;
constexpr int HP = 2;
constexpr int SD = 4;
constexpr int PD = 3;
constexpr int FC = 16;
constexpr int NC = 32 / FC;
constexpr int AS = 528;
constexpr int FR = (NW - 1) * 32;
constexpr int EARLY = SEG - FR / (NW * U);
constexpr int NF = H * (D / FC);
constexpr int GY = H + (H * EARLY + NF + SEG - 1) / SEG;
constexpr int CB = 10;
static_assert(FR % (NW * U) == 0 && (H - 1) * (SEG / H) <= EARLY && EARLY / NC < 255 && H + HP + SD <= GY && FC == 16 && CL == 2, "layout");
constexpr int SPIN_LIMIT = 1 << 22;

struct Scratch {
    unsigned cnt[256];
    float4 wts[H * (S / 4) * 2];
    float logits[H * S];
    unsigned long long acc[H * NC * (D / 16) * AS];
    float2 corr[H * 2];
};
__device__ __align__(1024) Scratch g_scr;

__device__ __forceinline__ uint64_t pol_first() {
    uint64_t p; asm("createpolicy.fractional.L2::evict_first.b64 %0, 1.0;" : "=l"(p)); return p;
}
__device__ __forceinline__ uint64_t pol_normal() {
    uint64_t p; asm("createpolicy.fractional.L2::evict_normal.b64 %0, 1.0;" : "=l"(p)); return p;
}
__device__ __forceinline__ int4 ld_stream(const int4* p, uint64_t pol) {
    int4 v;
    asm volatile("ld.global.nc.L1::no_allocate.L2::cache_hint.v4.s32 {%0,%1,%2,%3}, [%4], %5;"
                 : "=r"(v.x), "=r"(v.y), "=r"(v.z), "=r"(v.w) : "l"(p), "l"(pol));
    return v;
}
__device__ __forceinline__ int4 ld_stream(const int4* p) {
    int4 v;
    asm volatile("ld.global.nc.L1::no_allocate.v4.s32 {%0,%1,%2,%3}, [%4];"
                 : "=r"(v.x), "=r"(v.y), "=r"(v.z), "=r"(v.w) : "l"(p));
    return v;
}
__device__ __forceinline__ uint2 ld_nc8(const void* p) {
    uint2 v;
    asm volatile("ld.global.nc.v2.u32 {%0,%1}, [%2];" : "=r"(v.x), "=r"(v.y) : "l"(p));
    return v;
}
__device__ __forceinline__ uint2 ld_nc8(const void* p, uint64_t pol) {
    uint2 v;
    asm volatile("ld.global.nc.L2::cache_hint.v2.u32 {%0,%1}, [%2], %3;" : "=r"(v.x), "=r"(v.y) : "l"(p), "l"(pol));
    return v;
}
__device__ __forceinline__ uint4 ld_nc16(const void* p) {
    uint4 v;
    asm volatile("ld.global.nc.v4.u32 {%0,%1,%2,%3}, [%4];"
                 : "=r"(v.x), "=r"(v.y), "=r"(v.z), "=r"(v.w) : "l"(p));
    return v;
}
__device__ __forceinline__ uint4 ld_nc16_na(const void* p) {
    uint4 v;
    asm volatile("ld.global.nc.L1::no_allocate.v4.u32 {%0,%1,%2,%3}, [%4];"
                 : "=r"(v.x), "=r"(v.y), "=r"(v.z), "=r"(v.w) : "l"(p));
    return v;
}
__device__ __forceinline__ uint2 ld_rlx8(const void* p) {
    uint2 v;
    asm volatile("ld.relaxed.gpu.global.v2.u32 {%0,%1}, [%2];" : "=r"(v.x), "=r"(v.y) : "l"(p) : "memory");
    return v;
}
__device__ __forceinline__ uint4 ld_rlx16(const void* p) {
    uint4 v;
    asm volatile("ld.relaxed.gpu.global.v4.u32 {%0,%1,%2,%3}, [%4];"
                 : "=r"(v.x), "=r"(v.y), "=r"(v.z), "=r"(v.w) : "l"(p) : "memory");
    return v;
}
__device__ __forceinline__ void st_rlx64(void* p, unsigned long long v) {
    asm volatile("st.relaxed.gpu.global.u64 [%0], %1;" :: "l"(p), "l"(v) : "memory");
}
__device__ __forceinline__ void st_rlx8(void* p, uint32_t a, uint32_t b) {
    asm volatile("st.relaxed.gpu.global.v2.u32 [%0], {%1,%2};" :: "l"(p), "r"(a), "r"(b) : "memory");
}
__device__ __forceinline__ void st_rlx16(void* p, uint32_t a, uint32_t b, uint32_t c, uint32_t d) {
    asm volatile("st.relaxed.gpu.global.v4.u32 [%0], {%1,%2,%3,%4};" :: "l"(p), "r"(a), "r"(b), "r"(c), "r"(d) : "memory");
}
__device__ __forceinline__ uint32_t bad4(const uint4& v, uint32_t tag) {
    return (v.x ^ tag) | (v.y ^ tag) | (v.z ^ tag) | (v.w ^ tag);
}
__device__ __forceinline__ uint32_t tagf(float x, uint32_t tag) { return (__float_as_uint(x) & ~3u) | tag; }
__device__ __forceinline__ float bf_lo(uint32_t x) { return __uint_as_float(x << 16); }
__device__ __forceinline__ float bf_hi(uint32_t x) { return __uint_as_float(x & 0xffff0000u); }
__device__ __forceinline__ float ex2(float x) { float y; asm("ex2.approx.ftz.f32 %0, %1;" : "=f"(y) : "f"(x)); return y; }
__device__ __forceinline__ uint32_t bf2_mul(uint32_t a, uint32_t b) {
    uint32_t r; asm("mul.rn.bf16x2 %0, %1, %2;" : "=r"(r) : "r"(a), "r"(b)); return r;
}
__device__ __forceinline__ uint32_t bf2_add(uint32_t a, uint32_t b) {
    uint32_t r; asm("add.rn.bf16x2 %0, %1, %2;" : "=r"(r) : "r"(a), "r"(b)); return r;
}

struct Params {
    const int4* qk;
    const int4* qv;
    Scratch* scr;
    const __nv_bfloat16* q;
    const __nv_bfloat16* qcos;
    const __nv_bfloat16* qsin;
    const __nv_bfloat16* kcos;
    const __nv_bfloat16* ksin;
    const __nv_bfloat16* ks;
    const __nv_bfloat16* kz;
    const __nv_bfloat16* vs;
    const __nv_bfloat16* vz;
    __nv_bfloat16* out;
};

__device__ __forceinline__ unsigned long long* acc_ptr(const Params& P, int hc, int col) {
    return P.scr->acc + (uint32_t)((hc * (D / 16) + (col >> 4)) * AS + (col & 15));
}
__device__ __forceinline__ uint32_t ld_cnt(const Params& P) {
    uint32_t c;
    asm volatile("ld.global.ca.u32 %0, [%1];" : "=r"(c) : "l"(P.scr->cnt));
    return c;
}
__device__ __forceinline__ uint32_t tag_of(uint32_t c) { return ((c / NF) + 1u) & 3u; }
__device__ __forceinline__ uint32_t f_block(uint32_t h) { return (H - 1 - h) * (SEG / H); }

#define SPLIT(p_) do { if ((p_) == nullptr) __trap(); } while (0)
__device__ __forceinline__ void k_role(const Params& P, uint32_t x, uint32_t y) {
    const uint32_t w = threadIdx.x >> 5, lane = threadIdx.x & 31;
    const uint32_t h = (y & ~(HP - 1u)) + w % HP, r0 = ((y % HP * SEG + x) * (NW / HP) + w / HP) * U;
    const uint32_t row = h * S + r0;
    const uint32_t cnt = ld_cnt(P);
    const uint2 qq = ld_nc8(P.q + (h * D + lane * 4));
    const uint2 qp = ld_nc8(P.q + (h * D + (lane ^ 16) * 4));
    const uint2 qc = ld_nc8(P.qcos + lane * 4);
    const uint2 qs = ld_nc8(P.qsin + lane * 4);
    int4 kv[U];
    const int4* src = P.qk + (row * 32 + lane);
    SPLIT(P.qk);
#pragma unroll
    for (int u = 0; u < U; u++) kv[u] = ld_stream(src + u * 32, pol_first());
    SPLIT(P.kcos);
    uint2 cs[U], sn[U];
    const uint64_t pol = y >= H - HP ? pol_first() : pol_normal();
    const __nv_bfloat16* cp = P.kcos + (r0 * D + lane * 4);
    const __nv_bfloat16* sp = P.ksin + (r0 * D + (lane ^ 16) * 4);
#pragma unroll
    for (int u = 0; u < U; u++) {
        cs[u] = ld_nc8(cp + u * D, pol);
        sn[u] = ld_nc8(sp + u * D, pol);
    }
    const uint4 z4 = ld_nc16_na(P.kz + row * 2);
    const uint4 s4 = ld_nc16_na(P.ks + row * 2);
    const uint32_t zz[U] = {z4.x, z4.y, z4.z, z4.w}, sc[U] = {s4.x, s4.y, s4.z, s4.w};
    const uint32_t neg = (lane < 16) ? 0x80008000u : 0u;
    uint2 qr;
    qr.x = bf2_add(bf2_mul(qq.x, qc.x), bf2_mul(qp.x ^ neg, qs.x));
    qr.y = bf2_add(bf2_mul(qq.y, qc.y), bf2_mul(qp.y ^ neg, qs.y));
    uint2 qo;
    qo.x = __shfl_xor_sync(0xffffffffu, qr.x, 16);
    qo.y = __shfl_xor_sync(0xffffffffu, qr.y, 16);
    const float c = 0.08838834764831845f * 1.4426950408889634f;
    const float cb = (lane < 16) ? c : -c;
    const float qa0 = bf_lo(qr.x) * c, qa1 = bf_hi(qr.x) * c, qa2 = bf_lo(qr.y) * c, qa3 = bf_hi(qr.y) * c;
    const float qb0 = bf_lo(qo.x) * cb, qb1 = bf_hi(qo.x) * cb, qb2 = bf_lo(qo.y) * cb, qb3 = bf_hi(qo.y) * cb;
    const uint32_t sel = (lane < 16) ? 0x1044u : 0x3244u;

    float acc[U];
#pragma unroll
    for (int u = 0; u < U; u++) {
        const float z = __uint_as_float(__byte_perm(zz[u], 0u, sel));
        const float s = __uint_as_float(__byte_perm(sc[u], 0u, sel));
        const float a0 = fmaf(qa0, bf_lo(cs[u].x), qb0 * bf_lo(sn[u].x));
        const float a1 = fmaf(qa1, bf_hi(cs[u].x), qb1 * bf_hi(sn[u].x));
        const float a2 = fmaf(qa2, bf_lo(cs[u].y), qb2 * bf_lo(sn[u].y));
        const float a3 = fmaf(qa3, bf_hi(cs[u].y), qb3 * bf_hi(sn[u].y));
        float t = ((float)kv[u].x - z) * a0;
        t = fmaf((float)kv[u].y - z, a1, t);
        t = fmaf((float)kv[u].z - z, a2, t);
        t = fmaf((float)kv[u].w - z, a3, t);
        acc[u] = t * s;
    }
    const bool up = (lane & 16) != 0, up2 = (lane & 8) != 0;
    const float a = (up ? acc[2] : acc[0]) + __shfl_xor_sync(0xffffffffu, up ? acc[0] : acc[2], 16);
    const float b = (up ? acc[3] : acc[1]) + __shfl_xor_sync(0xffffffffu, up ? acc[1] : acc[3], 16);
    float lg = (up2 ? b : a) + __shfl_xor_sync(0xffffffffu, up2 ? a : b, 8);
#pragma unroll
    for (int off = 4; off > 0; off >>= 1) lg += __shfl_xor_sync(0xffffffffu, lg, off);
    asm volatile("{\n.reg .pred p;\nsetp.eq.u32 p, %2, 0;\n@p st.relaxed.gpu.global.u32 [%0], %1;\n}"
                 :: "l"(P.scr->logits + (row + (lane >> 3))), "r"(tagf(lg, tag_of(cnt))), "r"(lane & 7) : "memory");
}

__device__ __forceinline__ float block_sum(float x, float* s_red) {
#pragma unroll
    for (int o = 1; o < 32; o <<= 1) x += __shfl_xor_sync(0xffffffffu, x, o);
    if ((threadIdx.x & 31) == 0) s_red[threadIdx.x >> 5] = x;
    __syncthreads();
    const float4 a = *(const float4*)(s_red), b = *(const float4*)(s_red + 4);
    return ((a.x + a.y) + (a.z + a.w)) + ((b.x + b.y) + (b.z + b.w));
}

__device__ __forceinline__ void s_role(const Params& P, int h, float* sm) {
    constexpr int NB = S / (4 * NT);
    const int t = threadIdx.x;
    const uint32_t tag = tag_of(ld_cnt(P));
#pragma unroll
    for (int i = 0; i < (NC * D + NT - 1) / NT; i++)
        if (t + i * NT < NC * D) st_rlx64(acc_ptr(P, h * NC + (t + i * NT) / D, t % D), tag << 8);
    __threadfence();
    const float* lp = P.scr->logits + (h * S + t * 4);
    uint4 lg[NB];
    for (int it = 0;; it++) {
        uint32_t bad = 0;
#pragma unroll
        for (int j = 0; j < NB; j++) lg[j] = ld_rlx16(lp + j * (4 * NT));
#pragma unroll
        for (int j = 0; j < NB; j++) bad |= bad4(lg[j], tag);
        if (!__any_sync(0xffffffffu, bad & 3u)) break;
        if (it > SPIN_LIMIT) break;
        __nanosleep(500);
    }
    float m = __uint_as_float(lg[0].x);
#pragma unroll
    for (int j = 0; j < NB; j++)
        m = fmaxf(fmaxf(m, fmaxf(__uint_as_float(lg[j].x), __uint_as_float(lg[j].y))),
                  fmaxf(__uint_as_float(lg[j].z), __uint_as_float(lg[j].w)));
#pragma unroll
    for (int o = 1; o < 32; o <<= 1) m = fmaxf(m, __shfl_xor_sync(0xffffffffu, m, o));
    if ((t & 31) == 0) sm[t >> 5] = m;
    __syncthreads();
    {
        const float4 a = *(const float4*)(sm), b = *(const float4*)(sm + 4);
        m = fmaxf(fmaxf(fmaxf(a.x, a.y), fmaxf(a.z, a.w)), fmaxf(fmaxf(b.x, b.y), fmaxf(b.z, b.w)));
    }
    float p[NB][4];
    float l = 0.f;
#pragma unroll
    for (int j = 0; j < NB; j++) {
        p[j][0] = ex2(__uint_as_float(lg[j].x) - m);
        p[j][1] = ex2(__uint_as_float(lg[j].y) - m);
        p[j][2] = ex2(__uint_as_float(lg[j].z) - m);
        p[j][3] = ex2(__uint_as_float(lg[j].w) - m);
        l += (p[j][0] + p[j][1]) + (p[j][2] + p[j][3]);
    }
    const float inv = 1.f / block_sum(l, sm + NW);
    const __nv_bfloat16* vsp = P.vs + (h * S + t * 4) * 2;
    const __nv_bfloat16* vzp = P.vz + (h * S + t * 4) * 2;
    float a0 = 0.f, a1 = 0.f;
#pragma unroll
    for (int j0 = 0; j0 < NB; j0 += 4) {
        uint4 sv[4];
#pragma unroll
        for (int k = 0; k < 4; k++) sv[k] = ld_nc16(vsp + (j0 + k) * (8 * NT));
#pragma unroll
        for (int k = 0; k < 4; k++) {
            const uint32_t sc[4] = {sv[k].x, sv[k].y, sv[k].z, sv[k].w};
#pragma unroll
            for (int i = 0; i < 4; i++) {
                a0 = fmaf(p[j0 + k][i], fabsf(bf_lo(sc[i])), a0);
                a1 = fmaf(p[j0 + k][i], fabsf(bf_hi(sc[i])), a1);
            }
        }
    }
    const uint32_t e0 = min(max(__float_as_uint(block_sum(a0 * inv, sm + 2 * NW)) >> 23, 22u), 254u);
    const uint32_t e1 = min(max(__float_as_uint(block_sum(a1 * inv, sm + 3 * NW)) >> 23, 22u), 254u);
    const float i0 = inv * __uint_as_float((274u - e0) << 23), i1 = inv * __uint_as_float((274u - e1) << 23);
    float c0 = 0.f, c1 = 0.f;
    float4* wp = P.scr->wts + (h * (S / 4) + t) * 2;
#pragma unroll
    for (int j0 = 0; j0 < NB; j0 += 2) {
        uint4 sv[2], zv[2];
#pragma unroll
        for (int k = 0; k < 2; k++) {
            sv[k] = ld_nc16(vsp + (j0 + k) * (8 * NT));
            zv[k] = ld_nc16_na(vzp + (j0 + k) * (8 * NT));
        }
#pragma unroll
        for (int k = 0; k < 2; k++) {
            const int j = j0 + k;
            const uint32_t sc[4] = {sv[k].x, sv[k].y, sv[k].z, sv[k].w};
            const uint32_t zz[4] = {zv[k].x, zv[k].y, zv[k].z, zv[k].w};
            uint32_t w0[4], w1[4];
#pragma unroll
            for (int i = 0; i < 4; i++) {
                w0[i] = tagf(p[j][i] * i0 * bf_lo(sc[i]), tag);
                w1[i] = tagf(p[j][i] * i1 * bf_hi(sc[i]), tag);
                c0 = fmaf(__uint_as_float(w0[i]), bf_lo(zz[i]), c0);
                c1 = fmaf(__uint_as_float(w1[i]), bf_hi(zz[i]), c1);
            }
            st_rlx16(wp + j * (2 * NT), w0[0], w0[1], w0[2], w0[3]);
            st_rlx16(wp + j * (2 * NT) + 1, w1[0], w1[1], w1[2], w1[3]);
        }
    }
    c0 = block_sum(c0, sm + 4 * NW);
    c1 = block_sum(c1, sm + 5 * NW);
    if (t == 0) {
        st_rlx8(P.scr->corr + h * 2, tagf(c0, tag), ((e0 - 20u) << 23) | tag);
        st_rlx8(P.scr->corr + h * 2 + 1, tagf(c1, tag), ((e1 - 20u) << 23) | tag);
    }
}

__device__ __forceinline__ void v_role(const Params& P, uint32_t v, float* sm) {
    const int t = threadIdx.x, w = t >> 5, lane = t & 31;
    const uint32_t h = v / EARLY, j = v % EARLY;
    const uint32_t row = h * S + ((j + (j >= f_block(h) ? SEG - EARLY : 0)) * NW + w) * U;
    int4 vv[U];
    const int4* src = P.qv + (row * 32 + lane);
#pragma unroll
    for (int u = 0; u < U; u++) vv[u] = ld_stream(src + u * 32);
    const float4* wp = P.scr->wts + (row / 2 + (lane >> 4));
    uint4 wt = ld_rlx16(wp);
    const uint32_t tag = tag_of(ld_cnt(P));
    for (int it = 0; bad4(wt, tag) & 3u; it++) {
        if (it > SPIN_LIMIT) break;
        __nanosleep(100);
        wt = ld_rlx16(wp);
    }
    const float wu[4] = {__uint_as_float(wt.x), __uint_as_float(wt.y), __uint_as_float(wt.z), __uint_as_float(wt.w)};
    float o0 = (float)vv[0].x * wu[0], o1 = (float)vv[0].y * wu[0], o2 = (float)vv[0].z * wu[0], o3 = (float)vv[0].w * wu[0];
#pragma unroll
    for (int u = 1; u < U; u++) {
        o0 = fmaf((float)vv[u].x, wu[u], o0);
        o1 = fmaf((float)vv[u].y, wu[u], o1);
        o2 = fmaf((float)vv[u].z, wu[u], o2);
        o3 = fmaf((float)vv[u].w, wu[u], o3);
    }
    *(float4*)(sm + w * D + lane * 4) = make_float4(o0, o1, o2, o3);
    __syncthreads();
    if (t < D) {
        float r[NW];
#pragma unroll
        for (int k = 0; k < NW; k++) r[k] = sm[k * D + t];
        const float o = ((r[0] + r[1]) + (r[2] + r[3])) + ((r[4] + r[5]) + (r[6] + r[7]));
        const unsigned long long a = ((unsigned long long)__float2ll_rn(o) << CB) + 1ull;
        asm volatile("red.relaxed.gpu.global.add.L2::cache_hint.u64 [%0], %1, %2;"
                     :: "l"(acc_ptr(P, h * NC + j % NC, t)), "l"(a), "l"(pol_first()) : "memory");
    }
}

#define PIN32(x_) asm volatile("" : "+r"(x_))
#define PIN64(x_) asm volatile("" : "+l"(x_))
constexpr int PSTR = 20;
__device__ __forceinline__ int ld_half32(const int* p) {
    int v;
    asm volatile("ld.global.nc.L1::no_allocate.L2::128B.s32 %0, [%1];" : "=r"(v) : "l"(p));
    return v;
}
__device__ __forceinline__ float4 lds16(uint32_t a) {
    float4 v;
    asm volatile("ld.volatile.shared.v4.f32 {%0,%1,%2,%3}, [%4];" : "=f"(v.x), "=f"(v.y), "=f"(v.z), "=f"(v.w) : "r"(a) : "memory");
    return v;
}
__device__ __forceinline__ float acc_val(const uint2& a) {
    return fmaf((float)(int)a.y, (float)(1 << (32 - CB)), (float)(int)(a.x >> CB));
}
__device__ __forceinline__ void f_role(const Params& P, uint32_t f, float* sm) {
    const int t = threadIdx.x, w = t >> 5, lane = t & 31;
    const uint32_t h = f / (D / FC), c = f % (D / FC), g = c * FC / 64;
    uint32_t sb = (uint32_t)__cvta_generic_to_shared(sm);
    PIN32(sb);
    if (w == NW - 1) {
        const float2* cp = P.scr->corr + (h * 2 + g);
        const unsigned long long* ap = acc_ptr(P, h * NC, c * FC + lane % FC);
        uint2 a0 = ld_rlx8(ap), a1 = ld_rlx8(ap + (D / 16) * AS);
        uint2 cu = ld_rlx8(cp);
        const uint32_t tag = tag_of(ld_cnt(P));
        const uint32_t want0 = tag << 8 | (EARLY + 1) / NC, want1 = tag << 8 | EARLY / NC;
        uint32_t sa = sb + (lane % FC) * (PSTR * 4);
        __nv_bfloat16* op = P.out + (h * D + c * FC + lane);
        unsigned* cn = P.scr->cnt + lane;
        uint32_t one = 1;
        PIN32(sa); PIN64(op); PIN64(cn); PIN32(one);
        float own = 0.f;
        for (int it = 0;; it++) {
            const uint32_t bc = ((cu.x ^ tag) | (cu.y ^ tag)) & 3u;
            const uint32_t bl = bc | (((a0.x ^ want0) | (a1.x ^ want1)) & ((1u << CB) - 1u));
            own = (acc_val(a0) - __uint_as_float(cu.x)) + acc_val(a1);
            if (!__any_sync(0xffffffffu, bl)) break;
            if (it > SPIN_LIMIT) break;
            a0 = ld_rlx8(ap);
            a1 = ld_rlx8(ap + (D / 16) * AS);
            if (bc) cu = ld_rlx8(cp);
        }
        float scale = __uint_as_float(cu.y & ~3u);
        asm volatile("bar.sync 1, 256;" : "+f"(own), "+f"(scale) :: "memory");
        const float4 p0 = lds16(sa), p1 = lds16(sa + 16), p2 = lds16(sa + 32);
        float2 p3;
        asm volatile("ld.volatile.shared.v2.f32 {%0,%1}, [%2];" : "=f"(p3.x), "=f"(p3.y) : "r"(sa + 48) : "memory");
        const float x = ((((p0.x + p0.y) + (p0.z + p0.w)) + own) + ((p1.x + p1.y) + (p1.z + p1.w))) +
                        (((p2.x + p2.y) + (p2.z + p2.w)) + (p3.x + p3.y));
        asm volatile("{\n.reg .pred p;\n.reg .b32 r;\nsetp.lt.u32 p, %3, %4;\ncvt.rn.bf16x2.f32 r, %1, %1;\n@p st.global.u16 [%0], r;\nred.relaxed.gpu.global.add.u32 [%2], %5;\n}"
                     :: "l"(op), "f"(x * scale), "l"(cn), "r"(lane), "n"(FC), "r"(one) : "memory");
        return;
    }
    constexpr int RL = 16;
    const uint32_t row = h * S + f_block(h) * (NW * U) + w * 32 + (lane & 16);
    const int* src = (const int*)P.qv + (row * D + c * FC + lane % FC);
    uint32_t sa = sb + ((lane % FC) * PSTR + w * 2 + lane / FC) * 4;
    const float4* wp = P.scr->wts + (row / 2 + g);
    uint4 wt[RL / 4];
    int vv[RL];
#pragma unroll
    for (int u = 0; u < RL; u++) vv[u] = ld_half32(src + u * D);
#pragma unroll
    for (int k = 0; k < RL / 4; k++) wt[k] = ld_rlx16(wp + k * 2);
    const uint32_t tag = tag_of(ld_cnt(P));
    PIN32(sa);
    for (int it = 0; (bad4(wt[0], tag) | bad4(wt[1], tag) | bad4(wt[2], tag) | bad4(wt[3], tag)) & 3u; it++) {
        if (it > SPIN_LIMIT) break;
        __nanosleep(100);
#pragma unroll
        for (int k = 0; k < RL / 4; k++) wt[k] = ld_rlx16(wp + k * 2);
    }
    __syncwarp();
    float o0 = (float)vv[0] * __uint_as_float(wt[0].x), o1 = (float)vv[1] * __uint_as_float(wt[0].y);
    float o2 = (float)vv[2] * __uint_as_float(wt[0].z), o3 = (float)vv[3] * __uint_as_float(wt[0].w);
#pragma unroll
    for (int k = 1; k < RL / 4; k++) {
        o0 = fmaf((float)vv[4 * k], __uint_as_float(wt[k].x), o0);
        o1 = fmaf((float)vv[4 * k + 1], __uint_as_float(wt[k].y), o1);
        o2 = fmaf((float)vv[4 * k + 2], __uint_as_float(wt[k].z), o2);
        o3 = fmaf((float)vv[4 * k + 3], __uint_as_float(wt[k].w), o3);
    }
    asm volatile("st.volatile.shared.f32 [%0], %1;\nbar.arrive 1, 256;" :: "r"(sa), "f"((o0 + o1) + (o2 + o3)) : "memory");
}

__global__ void __cluster_dims__(CL, 1, 1) __launch_bounds__(NT, 4) attn_kernel(const Params P) {
    __shared__ __align__(16) float sm[NW * D];
    const uint32_t x = blockIdx.x, y = blockIdx.y;
    if (x >= SEG) {
        const int h = (int)y - (HP + SD);
        if (x == SEG + 1 && y + PD < H && threadIdx.x < 2 * HP) {
            const uint32_t yy = y + PD, i = threadIdx.x;
            const __nv_bfloat16* a = (i >= HP ? P.ks : P.kz) + (((yy & ~(HP - 1u)) + i % HP) * S + yy % HP * (S / HP)) * 2;
            asm volatile("cp.async.bulk.prefetch.L2.global [%0], %1;" :: "l"(a), "r"(S / HP * 4) : "memory");
        }
        if (x == SEG && h >= 0 && h < H) s_role(P, h, sm);
        return;
    }
    if (y >= H) {
        const uint32_t v = (y - H) * SEG + x;
        if (v < H * EARLY) v_role(P, v, sm);
        else if (v < H * EARLY + NF) f_role(P, v - H * EARLY, sm);
        return;
    }
    k_role(P, x, y);
}

}

extern "C" void kernel_launch(void* const* d_in, const int* in_sizes, int n_in, void* d_out, int out_size) {
    (void)in_sizes; (void)n_in; (void)out_size;
    Params P;
    P.q = (const __nv_bfloat16*)d_in[0];
    P.qk = (const int4*)d_in[1];
    P.ks = (const __nv_bfloat16*)d_in[2];
    P.kz = (const __nv_bfloat16*)d_in[3];
    P.qv = (const int4*)d_in[4];
    P.vs = (const __nv_bfloat16*)d_in[5];
    P.vz = (const __nv_bfloat16*)d_in[6];
    P.qcos = (const __nv_bfloat16*)d_in[7];
    P.qsin = (const __nv_bfloat16*)d_in[8];
    P.kcos = (const __nv_bfloat16*)d_in[9];
    P.ksin = (const __nv_bfloat16*)d_in[10];
    P.out = (__nv_bfloat16*)d_out;
    void* scr = nullptr;
    cudaGetSymbolAddress(&scr, g_scr);
    P.scr = (Scratch*)scr;
    attn_kernel<<<dim3(GX, GY), NT>>>(P);
}
```

```cpp
#include <cuda_runtime.h>
#include <cuda_bf16.h>
#include <stdint.h>

namespace {

constexpr int H = 32, S = 8192, D = 128;
constexpr int NW = 8;
constexpr int NT = NW * 32;
constexpr int U = 4;
constexpr int SEG = S / (NW * U);
constexpr int CL = 2;
constexpr int GX = SEG + CL;
constexpr int HP = 2;
constexpr int SD = 4;
constexpr int PD = 3;
constexpr int FC = 16;
constexpr int NC = 32 / FC;
constexpr int AS = 528;
constexpr int FR = (NW - 1) * 32;
constexpr int EARLY = SEG - FR / (NW * U);
constexpr int NF = H * (D / FC);
constexpr int GY = 2 * H + 1;
constexpr int CB = 10;
static_assert(FR % (NW * U) == 0 && (H - 1) * (SEG / H) <= EARLY && EARLY / NC < 255 && H + HP + SD <= GY, "layout");
static_assert(FC == 16 && CL == 2 && HP == 2 && U == 4 && NW == 8 && NF == SEG && (SEG / H) % NC == 0, "layout");
constexpr int SPIN_LIMIT = 1 << 22;

struct Scratch {
    unsigned cnt[256];
    float4 wts[H * (S / 4) * 2];
    float logits[H * S];
    unsigned long long acc[H * NC * (D / 16) * AS];
    float2 corr[H * 2];
};
__device__ __align__(1024) Scratch g_scr;

__device__ __forceinline__ uint64_t pol_first() {
    uint64_t p; asm("createpolicy.fractional.L2::evict_first.b64 %0, 1.0;" : "=l"(p)); return p;
}
__device__ __forceinline__ uint64_t pol_normal() {
    uint64_t p; asm("createpolicy.fractional.L2::evict_normal.b64 %0, 1.0;" : "=l"(p)); return p;
}
__device__ __forceinline__ uint2 ld_nc8(const void* p) {
    uint2 v;
    asm volatile("ld.global.nc.v2.u32 {%0,%1}, [%2];" : "=r"(v.x), "=r"(v.y) : "l"(p));
    return v;
}
__device__ __forceinline__ uint2 ld_nc8(const void* p, uint64_t pol) {
    uint2 v;
    asm volatile("ld.global.nc.L2::cache_hint.v2.u32 {%0,%1}, [%2], %3;" : "=r"(v.x), "=r"(v.y) : "l"(p), "l"(pol));
    return v;
}
__device__ __forceinline__ uint4 ld_nc16(const void* p) {
    uint4 v;
    asm volatile("ld.global.nc.v4.u32 {%0,%1,%2,%3}, [%4];"
                 : "=r"(v.x), "=r"(v.y), "=r"(v.z), "=r"(v.w) : "l"(p));
    return v;
}
__device__ __forceinline__ uint4 ld_nc16_na(const void* p) {
    uint4 v;
    asm volatile("ld.global.nc.L1::no_allocate.v4.u32 {%0,%1,%2,%3}, [%4];"
                 : "=r"(v.x), "=r"(v.y), "=r"(v.z), "=r"(v.w) : "l"(p));
    return v;
}
__device__ __forceinline__ uint2 ld_rlx8(const void* p) {
    uint2 v;
    asm volatile("ld.relaxed.gpu.global.v2.u32 {%0,%1}, [%2];" : "=r"(v.x), "=r"(v.y) : "l"(p) : "memory");
    return v;
}
__device__ __forceinline__ uint4 ld_rlx16(const void* p) {
    uint4 v;
    asm volatile("ld.relaxed.gpu.global.v4.u32 {%0,%1,%2,%3}, [%4];"
                 : "=r"(v.x), "=r"(v.y), "=r"(v.z), "=r"(v.w) : "l"(p) : "memory");
    return v;
}
__device__ __forceinline__ void st_rlx64(void* p, unsigned long long v) {
    asm volatile("st.relaxed.gpu.global.u64 [%0], %1;" :: "l"(p), "l"(v) : "memory");
}
__device__ __forceinline__ void st_rlx8(void* p, uint32_t a, uint32_t b) {
    asm volatile("st.relaxed.gpu.global.v2.u32 [%0], {%1,%2};" :: "l"(p), "r"(a), "r"(b) : "memory");
}
__device__ __forceinline__ void st_rlx16(void* p, uint32_t a, uint32_t b, uint32_t c, uint32_t d) {
    asm volatile("st.relaxed.gpu.global.v4.u32 [%0], {%1,%2,%3,%4};" :: "l"(p), "r"(a), "r"(b), "r"(c), "r"(d) : "memory");
}
__device__ __forceinline__ uint32_t bad4(const uint4& v, uint32_t tag) {
    return (v.x ^ tag) | (v.y ^ tag) | (v.z ^ tag) | (v.w ^ tag);
}
__device__ __forceinline__ uint32_t tagf(float x, uint32_t tag) { return (__float_as_uint(x) & ~3u) | tag; }
__device__ __forceinline__ float bf_lo(uint32_t x) { return __uint_as_float(x << 16); }
__device__ __forceinline__ float bf_hi(uint32_t x) { return __uint_as_float(x & 0xffff0000u); }
__device__ __forceinline__ float ex2(float x) { float y; asm("ex2.approx.ftz.f32 %0, %1;" : "=f"(y) : "f"(x)); return y; }
__device__ __forceinline__ uint32_t bf2_mul(uint32_t a, uint32_t b) {
    uint32_t r; asm("mul.rn.bf16x2 %0, %1, %2;" : "=r"(r) : "r"(a), "r"(b)); return r;
}
__device__ __forceinline__ uint32_t bf2_add(uint32_t a, uint32_t b) {
    uint32_t r; asm("add.rn.bf16x2 %0, %1, %2;" : "=r"(r) : "r"(a), "r"(b)); return r;
}

struct __align__(16) Params {
    const int4* qk;
    Scratch* scr;
    const int4* qv;
    Scratch* scr2;
    const __nv_bfloat16* q;
    const __nv_bfloat16* qcos;
    const __nv_bfloat16* qsin;
    const __nv_bfloat16* kcos;
    const __nv_bfloat16* ksin;
    const __nv_bfloat16* ks;
    const __nv_bfloat16* kz;
    const __nv_bfloat16* vs;
    const __nv_bfloat16* vz;
    __nv_bfloat16* out;
    void* pad[2];
};

__device__ __forceinline__ unsigned long long* acc_ptr(const Params& P, int hc, int col) {
    return P.scr->acc + (uint32_t)((hc * (D / 16) + (col >> 4)) * AS + (col & 15));
}
__device__ __forceinline__ uint32_t ld_cnt(const Params& P) {
    uint32_t c;
    asm volatile("ld.global.ca.u32 %0, [%1];" : "=r"(c) : "l"(P.scr->cnt));
    return c;
}
__device__ __forceinline__ uint32_t tag_of(uint32_t c) { return ((c / NF) + 1u) & 3u; }
__device__ __forceinline__ uint32_t f_block(uint32_t h) { return (H - 1 - h) * (SEG / H); }

#define BYTES(p_, o_) ((const char*)(p_) + (uint32_t)(o_))
#define PIN32(x_) asm volatile("" : "+r"(x_))
#define PIN64(x_) asm volatile("" : "+l"(x_))
struct KAddr { const char *qa, *qb, *qc, *qs, *cp, *sp, *ks, *kz; char* scr; };
template <bool LAST>
__device__ __forceinline__ void k_role(const Params& P, uint32_t off, const int4 (&kv)[U], KAddr A) {
    const uint32_t lane = threadIdx.x & 31;
    const uint32_t row = off >> 9;
    const uint2 qc = ld_nc8(A.qc), qs = ld_nc8(A.qs), qq = ld_nc8(A.qa), qp = ld_nc8(A.qb);
    uint32_t cnt;
    asm volatile("ld.global.ca.u32 %0, [%1];" : "=r"(cnt) : "l"(A.scr));
    uint2 cs[U], sn[U];
    const uint64_t pol = LAST ? pol_first() : pol_normal();
#pragma unroll
    for (int u = 0; u < U; u++) { cs[u] = ld_nc8(A.cp + u * (D * 2), pol); sn[u] = ld_nc8(A.sp + u * (D * 2), pol); }
    const uint4 z4 = ld_nc16_na(A.kz);
    const uint4 s4 = ld_nc16_na(A.ks);
    const uint32_t zz[U] = {z4.x, z4.y, z4.z, z4.w}, sc[U] = {s4.x, s4.y, s4.z, s4.w};
    const uint32_t neg = (lane < 16) ? 0x80008000u : 0u;
    uint2 qr;
    qr.x = bf2_add(bf2_mul(qq.x, qc.x), bf2_mul(qp.x ^ neg, qs.x));
    qr.y = bf2_add(bf2_mul(qq.y, qc.y), bf2_mul(qp.y ^ neg, qs.y));
    uint2 qo;
    qo.x = __shfl_xor_sync(0xffffffffu, qr.x, 16);
    qo.y = __shfl_xor_sync(0xffffffffu, qr.y, 16);
    const float c = 0.08838834764831845f * 1.4426950408889634f;
    const float cb = (lane < 16) ? c : -c;
    const float qa0 = bf_lo(qr.x) * c, qa1 = bf_hi(qr.x) * c, qa2 = bf_lo(qr.y) * c, qa3 = bf_hi(qr.y) * c;
    const float qb0 = bf_lo(qo.x) * cb, qb1 = bf_hi(qo.x) * cb, qb2 = bf_lo(qo.y) * cb, qb3 = bf_hi(qo.y) * cb;
    const uint32_t sel = (lane < 16) ? 0x1044u : 0x3244u;

    float acc[U];
#pragma unroll
    for (int u = 0; u < U; u++) {
        const float z = __uint_as_float(__byte_perm(zz[u], 0u, sel));
        const float s = __uint_as_float(__byte_perm(sc[u], 0u, sel));
        const float a0 = fmaf(qa0, bf_lo(cs[u].x), qb0 * bf_lo(sn[u].x));
        const float a1 = fmaf(qa1, bf_hi(cs[u].x), qb1 * bf_hi(sn[u].x));
        const float a2 = fmaf(qa2, bf_lo(cs[u].y), qb2 * bf_lo(sn[u].y));
        const float a3 = fmaf(qa3, bf_hi(cs[u].y), qb3 * bf_hi(sn[u].y));
        float t = ((float)kv[u].x - z) * a0;
        t = fmaf((float)kv[u].y - z, a1, t);
        t = fmaf((float)kv[u].z - z, a2, t);
        t = fmaf((float)kv[u].w - z, a3, t);
        acc[u] = t * s;
    }
    const bool up = (lane & 16) != 0, up2 = (lane & 8) != 0;
    const float a = (up ? acc[2] : acc[0]) + __shfl_xor_sync(0xffffffffu, up ? acc[0] : acc[2], 16);
    const float b = (up ? acc[3] : acc[1]) + __shfl_xor_sync(0xffffffffu, up ? acc[1] : acc[3], 16);
    float lg = (up2 ? b : a) + __shfl_xor_sync(0xffffffffu, up2 ? a : b, 8);
#pragma unroll
    for (int off = 4; off > 0; off >>= 1) lg += __shfl_xor_sync(0xffffffffu, lg, off);
    asm volatile("{\n.reg .pred p;\nsetp.eq.u32 p, %2, 0;\n@p st.relaxed.gpu.global.u32 [%0], %1;\n}"
                 :: "l"(P.scr->logits + (row + (lane >> 3))), "r"(tagf(lg, tag_of(cnt))), "r"(lane & 7) : "memory");
}

__device__ __forceinline__ float block_sum(float x, float* s_red) {
#pragma unroll
    for (int o = 1; o < 32; o <<= 1) x += __shfl_xor_sync(0xffffffffu, x, o);
    if ((threadIdx.x & 31) == 0) s_red[threadIdx.x >> 5] = x;
    __syncthreads();
    const float4 a = *(const float4*)(s_red), b = *(const float4*)(s_red + 4);
    return ((a.x + a.y) + (a.z + a.w)) + ((b.x + b.y) + (b.z + b.w));
}

__device__ __forceinline__ void s_role(const Params& P, int h, float* sm) {
    constexpr int NB = S / (4 * NT);
    const int t = threadIdx.x;
    const uint32_t tag = tag_of(ld_cnt(P));
#pragma unroll
    for (int i = 0; i < (NC * D + NT - 1) / NT; i++)
        if (t + i * NT < NC * D) st_rlx64(acc_ptr(P, h * NC + (t + i * NT) / D, t % D), tag << 8);
    __threadfence();
    const float* lp = P.scr->logits + (h * S + t * 4);
    uint4 lg[NB];
    for (int it = 0;; it++) {
        uint32_t bad = 0;
#pragma unroll
        for (int j = 0; j < NB; j++) lg[j] = ld_rlx16(lp + j * (4 * NT));
#pragma unroll
        for (int j = 0; j < NB; j++) bad |= bad4(lg[j], tag);
        if (!__any_sync(0xffffffffu, bad & 3u)) break;
        if (it > SPIN_LIMIT) break;
        __nanosleep(500);
    }
    float m = __uint_as_float(lg[0].x);
#pragma unroll
    for (int j = 0; j < NB; j++)
        m = fmaxf(fmaxf(m, fmaxf(__uint_as_float(lg[j].x), __uint_as_float(lg[j].y))),
                  fmaxf(__uint_as_float(lg[j].z), __uint_as_float(lg[j].w)));
#pragma unroll
    for (int o = 1; o < 32; o <<= 1) m = fmaxf(m, __shfl_xor_sync(0xffffffffu, m, o));
    if ((t & 31) == 0) sm[t >> 5] = m;
    __syncthreads();
    {
        const float4 a = *(const float4*)(sm), b = *(const float4*)(sm + 4);
        m = fmaxf(fmaxf(fmaxf(a.x, a.y), fmaxf(a.z, a.w)), fmaxf(fmaxf(b.x, b.y), fmaxf(b.z, b.w)));
    }
    float p[NB][4];
    float l = 0.f;
#pragma unroll
    for (int j = 0; j < NB; j++) {
        p[j][0] = ex2(__uint_as_float(lg[j].x) - m);
        p[j][1] = ex2(__uint_as_float(lg[j].y) - m);
        p[j][2] = ex2(__uint_as_float(lg[j].z) - m);
        p[j][3] = ex2(__uint_as_float(lg[j].w) - m);
        l += (p[j][0] + p[j][1]) + (p[j][2] + p[j][3]);
    }
    float inv;
    asm("rcp.approx.ftz.f32 %0, %1;" : "=f"(inv) : "f"(block_sum(l, sm + NW)));
    const __nv_bfloat16* vsp = P.vs + (h * S + t * 4) * 2;
    const __nv_bfloat16* vzp = P.vz + (h * S + t * 4) * 2;
    float a0 = 0.f, a1 = 0.f;
#pragma unroll
    for (int j0 = 0; j0 < NB; j0 += 4) {
        uint4 sv[4];
#pragma unroll
        for (int k = 0; k < 4; k++) sv[k] = ld_nc16(vsp + (j0 + k) * (8 * NT));
#pragma unroll
        for (int k = 0; k < 4; k++) {
            const uint32_t sc[4] = {sv[k].x, sv[k].y, sv[k].z, sv[k].w};
#pragma unroll
            for (int i = 0; i < 4; i++) {
                a0 = fmaf(p[j0 + k][i], fabsf(bf_lo(sc[i])), a0);
                a1 = fmaf(p[j0 + k][i], fabsf(bf_hi(sc[i])), a1);
            }
        }
    }
    const uint32_t e0 = min(max(__float_as_uint(block_sum(a0 * inv, sm + 2 * NW)) >> 23, 22u), 254u);
    const uint32_t e1 = min(max(__float_as_uint(block_sum(a1 * inv, sm + 3 * NW)) >> 23, 22u), 254u);
    const float i0 = inv * __uint_as_float((274u - e0) << 23), i1 = inv * __uint_as_float((274u - e1) << 23);
    float c0 = 0.f, c1 = 0.f;
    float4* wp = P.scr->wts + (h * (S / 4) + t) * 2;
#pragma unroll 1
    for (int j0 = 0; j0 < NB; j0 += 2) {
        uint4 sv[2], zv[2], gv[2];
#pragma unroll
        for (int k = 0; k < 2; k++) {
            zv[k] = ld_nc16_na(vzp + (j0 + k) * (8 * NT));
            gv[k] = ld_rlx16(lp + (j0 + k) * (4 * NT));
            sv[k] = ld_nc16(vsp + (j0 + k) * (8 * NT));
        }
#pragma unroll
        for (int k = 0; k < 2; k++) {
            const int j = j0 + k;
            const uint32_t sc[4] = {sv[k].x, sv[k].y, sv[k].z, sv[k].w};
            const uint32_t zz[4] = {zv[k].x, zv[k].y, zv[k].z, zv[k].w};
            const uint32_t gg[4] = {gv[k].x, gv[k].y, gv[k].z, gv[k].w};
            uint32_t w0[4], w1[4];
#pragma unroll
            for (int i = 0; i < 4; i++) {
                const float pp = ex2(__uint_as_float(gg[i]) - m);
                w0[i] = tagf(pp * i0 * bf_lo(sc[i]), tag);
                w1[i] = tagf(pp * i1 * bf_hi(sc[i]), tag);
                c0 = fmaf(__uint_as_float(w0[i]), bf_lo(zz[i]), c0);
                c1 = fmaf(__uint_as_float(w1[i]), bf_hi(zz[i]), c1);
            }
            st_rlx16(wp + j * (2 * NT), w0[0], w0[1], w0[2], w0[3]);
            st_rlx16(wp + j * (2 * NT) + 1, w1[0], w1[1], w1[2], w1[3]);
        }
    }
    c0 = block_sum(c0, sm + 4 * NW);
    c1 = block_sum(c1, sm + 5 * NW);
    if (t == 0) {
        st_rlx8(P.scr->corr + h * 2, tagf(c0, tag), ((e0 - 20u) << 23) | tag);
        st_rlx8(P.scr->corr + h * 2 + 1, tagf(c1, tag), ((e1 - 20u) << 23) | tag);
    }
}

__device__ __forceinline__ void v_role(const Params& P, uint32_t off, const int4 (&vv)[U], float* sm) {
    const int t = threadIdx.x, w = t >> 5, lane = t & 31;
    const uint32_t h = off >> 22, j = blockIdx.x;
    const char* wp = BYTES(P.scr->wts, (off >> 11) * 32 + (lane & 16));
    uint4 wt = ld_rlx16(wp);
    const uint32_t tag = tag_of(ld_cnt(P));
    for (int it = 0; bad4(wt, tag) & 3u; it++) {
        if (it > SPIN_LIMIT) break;
        __nanosleep(100);
        wt = ld_rlx16(wp);
    }
    const float wu[4] = {__uint_as_float(wt.x), __uint_as_float(wt.y), __uint_as_float(wt.z), __uint_as_float(wt.w)};
    float o0 = (float)vv[0].x * wu[0], o1 = (float)vv[0].y * wu[0], o2 = (float)vv[0].z * wu[0], o3 = (float)vv[0].w * wu[0];
#pragma unroll
    for (int u = 1; u < U; u++) {
        o0 = fmaf((float)vv[u].x, wu[u], o0);
        o1 = fmaf((float)vv[u].y, wu[u], o1);
        o2 = fmaf((float)vv[u].z, wu[u], o2);
        o3 = fmaf((float)vv[u].w, wu[u], o3);
    }
    *(float4*)(sm + w * D + lane * 4) = make_float4(o0, o1, o2, o3);
    __syncthreads();
    if (t < D) {
        float r[NW];
#pragma unroll
        for (int k = 0; k < NW; k++) r[k] = sm[k * D + t];
        const float o = ((r[0] + r[1]) + (r[2] + r[3])) + ((r[4] + r[5]) + (r[6] + r[7]));
        const unsigned long long a = ((unsigned long long)__float2ll_rn(o) << CB) + 1ull;
        asm volatile("red.relaxed.gpu.global.add.L2::cache_hint.u64 [%0], %1, %2;"
                     :: "l"(acc_ptr(P, h * NC + j % NC, t)), "l"(a), "l"(pol_first()) : "memory");
    }
}

constexpr int PSTR = 20;
__device__ __forceinline__ int ld_half32(const int* p) {
    int v;
    asm volatile("ld.global.nc.L1::no_allocate.L2::128B.s32 %0, [%1];" : "=r"(v) : "l"(p));
    return v;
}
__device__ __forceinline__ float4 lds16(uint32_t a) {
    float4 v;
    asm volatile("ld.volatile.shared.v4.f32 {%0,%1,%2,%3}, [%4];" : "=f"(v.x), "=f"(v.y), "=f"(v.z), "=f"(v.w) : "r"(a) : "memory");
    return v;
}
__device__ __forceinline__ float acc_val(const uint2& a) {
    return fmaf((float)(int)a.y, (float)(1 << (32 - CB)), (float)(int)(a.x >> CB));
}
__device__ __forceinline__ void f_role(const Params& P, uint32_t f, float* sm) {
    const int t = threadIdx.x, w = t >> 5, lane = t & 31;
    const uint32_t h = f / (D / FC), c = f % (D / FC), g = c * FC / 64;
    uint32_t sb = (uint32_t)__cvta_generic_to_shared(sm);
    PIN32(sb);
    if (w == NW - 1) {
        const float2* cp = P.scr->corr + (h * 2 + g);
        const unsigned long long* ap = acc_ptr(P, h * NC, c * FC + lane % FC);
        uint2 a0 = ld_rlx8(ap), a1 = ld_rlx8(ap + (D / 16) * AS);
        uint2 cu = ld_rlx8(cp);
        const uint32_t tag = tag_of(ld_cnt(P));
        const uint32_t want0 = tag << 8 | EARLY / NC, want1 = tag << 8 | (EARLY + 1) / NC;
        uint32_t sa = sb + (lane % FC) * (PSTR * 4);
        __nv_bfloat16* op = P.out + (h * D + c * FC + lane);
        unsigned* cn = P.scr->cnt + lane;
        uint32_t one = 1;
        PIN32(sa); PIN64(op); PIN64(cn); PIN32(one);
        for (int it = 0; ((cu.x ^ tag) | (cu.y ^ tag)) & 3u; it++) {
            if (it > SPIN_LIMIT) break;
            cu = ld_rlx8(cp);
        }
        for (int it = 0;; it++) {
            if ((((a0.x ^ want0) | (a1.x ^ want1)) & ((1u << CB) - 1u)) == 0 || it > SPIN_LIMIT) break;
            a0 = ld_rlx8(ap);
            a1 = ld_rlx8(ap + (D / 16) * AS);
        }
        float own = (acc_val(a0) - __uint_as_float(cu.x)) + acc_val(a1);
        float scale = __uint_as_float(cu.y & ~3u);
        asm volatile("bar.sync 1, 256;" : "+f"(own), "+f"(scale) :: "memory");
        const float4 p0 = lds16(sa), p1 = lds16(sa + 16), p2 = lds16(sa + 32);
        float2 p3;
        asm volatile("ld.volatile.shared.v2.f32 {%0,%1}, [%2];" : "=f"(p3.x), "=f"(p3.y) : "r"(sa + 48) : "memory");
        const float x = ((((p0.x + p0.y) + (p0.z + p0.w)) + own) + ((p1.x + p1.y) + (p1.z + p1.w))) +
                        (((p2.x + p2.y) + (p2.z + p2.w)) + (p3.x + p3.y));
        asm volatile("{\n.reg .pred p;\n.reg .b32 r;\nsetp.lt.u32 p, %3, %4;\ncvt.rn.bf16x2.f32 r, %1, %1;\n@p st.global.u16 [%0], r;\nred.relaxed.gpu.global.add.u32 [%2], %5;\n}"
                     :: "l"(op), "f"(x * scale), "l"(cn), "r"(lane), "n"(FC), "r"(one) : "memory");
        return;
    }
    constexpr int RL = 16;
    const uint32_t row = h * S + f_block(h) * (NW * U) + w * 32 + (lane & 16);
    const int* src = (const int*)P.qv + (row * D + c * FC + lane % FC);
    uint32_t sa = sb + ((lane % FC) * PSTR + w * 2 + lane / FC) * 4;
    const float4* wp = P.scr->wts + (row / 2 + g);
    uint4 wt[RL / 4];
    int vv[RL];
#pragma unroll
    for (int u = 0; u < RL; u++) vv[u] = ld_half32(src + u * D);
#pragma unroll
    for (int k = 0; k < RL / 4; k++) wt[k] = ld_rlx16(wp + k * 2);
    const uint32_t tag = tag_of(ld_cnt(P));
    PIN32(sa);
    for (int it = 0; (bad4(wt[0], tag) | bad4(wt[1], tag) | bad4(wt[2], tag) | bad4(wt[3], tag)) & 3u; it++) {
        if (it > SPIN_LIMIT) break;
        __nanosleep(100);
#pragma unroll
        for (int k = 0; k < RL / 4; k++) wt[k] = ld_rlx16(wp + k * 2);
    }
    __syncwarp();
    float o0 = (float)vv[0] * __uint_as_float(wt[0].x), o1 = (float)vv[1] * __uint_as_float(wt[0].y);
    float o2 = (float)vv[2] * __uint_as_float(wt[0].z), o3 = (float)vv[3] * __uint_as_float(wt[0].w);
#pragma unroll
    for (int k = 1; k < RL / 4; k++) {
        o0 = fmaf((float)vv[4 * k], __uint_as_float(wt[k].x), o0);
        o1 = fmaf((float)vv[4 * k + 1], __uint_as_float(wt[k].y), o1);
        o2 = fmaf((float)vv[4 * k + 2], __uint_as_float(wt[k].z), o2);
        o3 = fmaf((float)vv[4 * k + 3], __uint_as_float(wt[k].w), o3);
    }
    asm volatile("st.volatile.shared.f32 [%0], %1;\nbar.arrive 1, 256;" :: "r"(sa), "f"((o0 + o1) + (o2 + o3)) : "memory");
}

__global__ void __cluster_dims__(CL, 1, 1) __launch_bounds__(NT, 4) attn_kernel(const __grid_constant__ Params P) {
    __shared__ __align__(16) float sm[NW * D];
    const uint32_t x = blockIdx.x, y = blockIdx.y, t = threadIdx.x;
    const uint32_t a = t * 16 + (t >> 5) * 1536;
    const uint32_t ko = a + (x << 13) + ((y + (y & ~1u)) << 21) + (t >> 7) * ((1u << 22) - (1u << 13));
    const uint32_t vo = a + (x << 14) + ((y - H) << 22);
    uint32_t off = y < H ? ko : vo;
    const ulonglong2* tab = (const ulonglong2*)&P + y / H;
    const ulonglong2 t0 = tab[0];
    const ulonglong2 t2 = tab[2], t3 = tab[3], t4 = tab[4], t5 = tab[5];
    const char* src = BYTES(t0.x, off);
    PIN64(src); PIN32(off);
    const bool other = x >= SEG || y >= 2 * H || x - f_block(y - H) < SEG - EARLY;
    int4 d[U];
    asm volatile("{\n.reg .pred p;\n.reg .b64 q;\nsetp.eq.u32 p, %17, 0;\ncreatepolicy.fractional.L2::evict_first.b64 q, 1.0;\n"
                 "@p ld.global.nc.L1::no_allocate.L2::cache_hint.v4.s32 {%0,%1,%2,%3}, [%16], q;\n"
                 "@p ld.global.nc.L1::no_allocate.L2::cache_hint.v4.s32 {%4,%5,%6,%7}, [%16+512], q;\n"
                 "@p ld.global.nc.L1::no_allocate.L2::cache_hint.v4.s32 {%8,%9,%10,%11}, [%16+1024], q;\n"
                 "@p ld.global.nc.L1::no_allocate.L2::cache_hint.v4.s32 {%12,%13,%14,%15}, [%16+1536], q;\n}"
                 : "=r"(d[0].x), "=r"(d[0].y), "=r"(d[0].z), "=r"(d[0].w), "=r"(d[1].x), "=r"(d[1].y), "=r"(d[1].z), "=r"(d[1].w),
                   "=r"(d[2].x), "=r"(d[2].y), "=r"(d[2].z), "=r"(d[2].w), "=r"(d[3].x), "=r"(d[3].y), "=r"(d[3].z), "=r"(d[3].w)
                 : "l"(src), "r"((uint32_t)other));
    if (other) {
        if (x >= SEG) {
            const int h = (int)y - (HP + SD);
            if (x == SEG + 1 && y + PD < H && threadIdx.x < 2 * HP) {
                const uint32_t yy = y + PD, i = threadIdx.x;
                const __nv_bfloat16* a = (i >= HP ? P.ks : P.kz) + (((yy & ~(HP - 1u)) + i % HP) * S + yy % HP * (S / HP)) * 2;
                asm volatile("cp.async.bulk.prefetch.L2.global [%0], %1;" :: "l"(a), "r"(S / HP * 4) : "memory");
            }
            if (x == SEG && h >= 0 && h < H) s_role(P, h, sm);
        } else if (y >= 2 * H) {
            f_role(P, x, sm);
        }
        return;
    }
    KAddr A;
    {
        const uint32_t l8 = (t & 31) * 8, qo = (off >> 22) * (D * 2) + l8, co = (off >> 1) & (S * D * 2 - 1);
        A.qa = BYTES(t2.x, qo); A.qb = BYTES(t2.x, qo ^ 128u); A.qc = BYTES(t2.y, l8); A.qs = BYTES(t3.x, l8);
        A.cp = BYTES(t3.y, co); A.sp = BYTES(t4.x, co ^ 128u);
        A.ks = BYTES(t4.y, (off >> 9) * 4); A.kz = BYTES(t5.x, (off >> 9) * 4);
        A.scr = (char*)t0.y;
    }
    asm volatile("" : "+l"(A.qa), "+l"(A.qb), "+l"(A.qc), "+l"(A.qs));
    asm volatile("" : "+l"(A.cp), "+l"(A.sp), "+l"(A.ks), "+l"(A.kz));
    if (y >= H - HP) {
        if (y >= H) v_role(P, off, d, sm);
        else k_role<true>(P, off, d, A);
        return;
    }
    k_role<false>(P, off, d, A);
}

}

extern "C" void kernel_launch(void* const* d_in, const int* in_sizes, int n_in, void* d_out, int out_size) {
    (void)in_sizes; (void)n_in; (void)out_size;
    Params P;
    P.q = (const __nv_bfloat16*)d_in[0];
    P.qk = (const int4*)d_in[1];
    P.ks = (const __nv_bfloat16*)d_in[2];
    P.kz = (const __nv_bfloat16*)d_in[3];
    P.qv = (const int4*)d_in[4];
    P.vs = (const __nv_bfloat16*)d_in[5];
    P.vz = (const __nv_bfloat16*)d_in[6];
    P.qcos = (const __nv_bfloat16*)d_in[7];
    P.qsin = (const __nv_bfloat16*)d_in[8];
    P.kcos = (const __nv_bfloat16*)d_in[9];
    P.ksin = (const __nv_bfloat16*)d_in[10];
    P.out = (__nv_bfloat16*)d_out;
    void* scr = nullptr;
    cudaGetSymbolAddress(&scr, g_scr);
    P.scr = P.scr2 = (Scratch*)scr;
    P.pad[0] = P.pad[1] = nullptr;
    attn_kernel<<<dim3(GX, GY), NT>>>(P);
}
```

```cpp
#include <cuda_runtime.h>
#include <cuda_bf16.h>
#include <stdint.h>

namespace {

constexpr int H = 32, S = 8192, D = 128;
constexpr int NW = 8;
constexpr int NT = NW * 32;
constexpr int U = 4;
constexpr int SEG = S / (NW * U);
constexpr int CL = 2;
constexpr int GX = SEG + CL;
constexpr int HP = 2;
constexpr int SD = 4;
constexpr int PD = 3;
constexpr int FC = 16;
constexpr int NC = 32 / FC;
constexpr int AS = 528;
constexpr int FR = (NW - 1) * 32;
constexpr int EARLY = SEG - FR / (NW * U);
constexpr int NF = H * (D / FC);
constexpr int GY = 2 * H + 1;
constexpr int CB = 10;
static_assert(FR % (NW * U) == 0 && (H - 1) * (SEG / H) <= EARLY && EARLY / NC < 255 && H + HP + SD <= GY, "layout");
static_assert(FC == 16 && CL == 2 && HP == 2 && U == 4 && NW == 8 && NF == SEG && (SEG / H) % NC == 0, "layout");
constexpr int SPIN_LIMIT = 1 << 22;

struct Scratch {
    unsigned cnt[256];
    float4 wts[H * (S / 4) * 2];
    float logits[H * S];
    unsigned long long acc[H * NC * (D / 16) * AS];
    float2 corr[H * 2];
};
__device__ __align__(1024) Scratch g_scr;

__device__ __forceinline__ uint64_t pol_first() {
    uint64_t p; asm("createpolicy.fractional.L2::evict_first.b64 %0, 1.0;" : "=l"(p)); return p;
}
__device__ __forceinline__ uint64_t pol_normal() {
    uint64_t p; asm("createpolicy.fractional.L2::evict_normal.b64 %0, 1.0;" : "=l"(p)); return p;
}
__device__ __forceinline__ uint2 ld_nc8(const void* p) {
    uint2 v;
    asm volatile("ld.global.nc.v2.u32 {%0,%1}, [%2];" : "=r"(v.x), "=r"(v.y) : "l"(p));
    return v;
}
__device__ __forceinline__ uint2 ld_nc8(const void* p, uint64_t pol) {
    uint2 v;
    asm volatile("ld.global.nc.L2::cache_hint.v2.u32 {%0,%1}, [%2], %3;" : "=r"(v.x), "=r"(v.y) : "l"(p), "l"(pol));
    return v;
}
__device__ __forceinline__ uint4 ld_nc16(const void* p) {
    uint4 v;
    asm volatile("ld.global.nc.v4.u32 {%0,%1,%2,%3}, [%4];"
                 : "=r"(v.x), "=r"(v.y), "=r"(v.z), "=r"(v.w) : "l"(p));
    return v;
}
__device__ __forceinline__ uint4 ld_nc16_na(const void* p) {
    uint4 v;
    asm volatile("ld.global.nc.L1::no_allocate.v4.u32 {%0,%1,%2,%3}, [%4];"
                 : "=r"(v.x), "=r"(v.y), "=r"(v.z), "=r"(v.w) : "l"(p));
    return v;
}
__device__ __forceinline__ uint2 ld_rlx8(const void* p) {
    uint2 v;
    asm volatile("ld.relaxed.gpu.global.v2.u32 {%0,%1}, [%2];" : "=r"(v.x), "=r"(v.y) : "l"(p) : "memory");
    return v;
}
__device__ __forceinline__ uint4 ld_rlx16(const void* p) {
    uint4 v;
    asm volatile("ld.relaxed.gpu.global.v4.u32 {%0,%1,%2,%3}, [%4];"
                 : "=r"(v.x), "=r"(v.y), "=r"(v.z), "=r"(v.w) : "l"(p) : "memory");
    return v;
}
__device__ __forceinline__ void st_rlx64(void* p, unsigned long long v) {
    asm volatile("st.relaxed.gpu.global.u64 [%0], %1;" :: "l"(p), "l"(v) : "memory");
}
__device__ __forceinline__ void st_rlx8(void* p, uint32_t a, uint32_t b) {
    asm volatile("st.relaxed.gpu.global.v2.u32 [%0], {%1,%2};" :: "l"(p), "r"(a), "r"(b) : "memory");
}
__device__ __forceinline__ void st_rlx16(void* p, uint32_t a, uint32_t b, uint32_t c, uint32_t d) {
    asm volatile("st.relaxed.gpu.global.v4.u32 [%0], {%1,%2,%3,%4};" :: "l"(p), "r"(a), "r"(b), "r"(c), "r"(d) : "memory");
}
__device__ __forceinline__ uint32_t bad4(const uint4& v, uint32_t tag) {
    return (v.x ^ tag) | (v.y ^ tag) | (v.z ^ tag) | (v.w ^ tag);
}
__device__ __forceinline__ uint32_t tagf(float x, uint32_t tag) { return (__float_as_uint(x) & ~3u) | tag; }
__device__ __forceinline__ float bf_lo(uint32_t x) { return __uint_as_float(x << 16); }
__device__ __forceinline__ float bf_hi(uint32_t x) { return __uint_as_float(x & 0xffff0000u); }
__device__ __forceinline__ float ex2(float x) { float y; asm("ex2.approx.ftz.f32 %0, %1;" : "=f"(y) : "f"(x)); return y; }
__device__ __forceinline__ uint32_t bf2_mul(uint32_t a, uint32_t b) {
    uint32_t r; asm("mul.rn.bf16x2 %0, %1, %2;" : "=r"(r) : "r"(a), "r"(b)); return r;
}
__device__ __forceinline__ uint32_t bf2_add(uint32_t a, uint32_t b) {
    uint32_t r; asm("add.rn.bf16x2 %0, %1, %2;" : "=r"(r) : "r"(a), "r"(b)); return r;
}

struct __align__(16) Params {
    const int4* qk;
    Scratch* scr;
    const int4* qv;
    Scratch* scr2;
    const __nv_bfloat16* q;
    const __nv_bfloat16* qcos;
    const __nv_bfloat16* qsin;
    const __nv_bfloat16* kcos;
    const __nv_bfloat16* ksin;
    const __nv_bfloat16* ks;
    const __nv_bfloat16* kz;
    const __nv_bfloat16* vs;
    const __nv_bfloat16* vz;
    __nv_bfloat16* out;
    void* pad;
    const int* qv2;
};

__device__ __forceinline__ unsigned long long* acc_ptr(const Params& P, int hc, int col) {
    return P.scr->acc + (uint32_t)((hc * (D / 16) + (col >> 4)) * AS + (col & 15));
}
__device__ __forceinline__ uint32_t ld_cnt(const Params& P) {
    uint32_t c;
    asm volatile("ld.global.ca.u32 %0, [%1];" : "=r"(c) : "l"(P.scr->cnt));
    return c;
}
__device__ __forceinline__ uint32_t tag_of(uint32_t c) { return ((c / NF) + 1u) & 3u; }
__device__ __forceinline__ uint32_t f_block(uint32_t h) { return (H - 1 - h) * (SEG / H); }

#define BYTES(p_, o_) ((const char*)(p_) + (uint32_t)(o_))
#define PIN32(x_) asm volatile("" : "+r"(x_))
#define PIN64(x_) asm volatile("" : "+l"(x_))
struct KAddr { const char *qa, *qb, *qc, *qs, *cp, *sp, *ks, *kz; char* scr; };
template <bool LAST>
__device__ __forceinline__ void k_role(const Params& P, uint32_t off, const int4 (&kv)[U], KAddr A) {
    const uint32_t lane = threadIdx.x & 31;
    const uint32_t row = off >> 9;
    const uint2 qc = ld_nc8(A.qc), qs = ld_nc8(A.qs), qq = ld_nc8(A.qa), qp = ld_nc8(A.qb);
    uint32_t cnt;
    asm volatile("ld.global.ca.u32 %0, [%1];" : "=r"(cnt) : "l"(A.scr));
    uint2 cs[U], sn[U];
    const uint64_t pol = LAST ? pol_first() : pol_normal();
#pragma unroll
    for (int u = 0; u < U; u++) { cs[u] = ld_nc8(A.cp + u * (D * 2), pol); sn[u] = ld_nc8(A.sp + u * (D * 2), pol); }
    const uint4 z4 = ld_nc16_na(A.kz);
    const uint4 s4 = ld_nc16_na(A.ks);
    const uint32_t zz[U] = {z4.x, z4.y, z4.z, z4.w}, sc[U] = {s4.x, s4.y, s4.z, s4.w};
    const uint32_t neg = (lane < 16) ? 0x80008000u : 0u;
    uint2 qr;
    qr.x = bf2_add(bf2_mul(qq.x, qc.x), bf2_mul(qp.x ^ neg, qs.x));
    qr.y = bf2_add(bf2_mul(qq.y, qc.y), bf2_mul(qp.y ^ neg, qs.y));
    uint2 qo;
    qo.x = __shfl_xor_sync(0xffffffffu, qr.x, 16);
    qo.y = __shfl_xor_sync(0xffffffffu, qr.y, 16);
    const float c = 0.08838834764831845f * 1.4426950408889634f;
    const float cb = (lane < 16) ? c : -c;
    const float qa0 = bf_lo(qr.x) * c, qa1 = bf_hi(qr.x) * c, qa2 = bf_lo(qr.y) * c, qa3 = bf_hi(qr.y) * c;
    const float qb0 = bf_lo(qo.x) * cb, qb1 = bf_hi(qo.x) * cb, qb2 = bf_lo(qo.y) * cb, qb3 = bf_hi(qo.y) * cb;
    const uint32_t sel = (lane < 16) ? 0x1044u : 0x3244u;

    float acc[U];
#pragma unroll
    for (int u = 0; u < U; u++) {
        const float z = __uint_as_float(__byte_perm(zz[u], 0u, sel));
        const float s = __uint_as_float(__byte_perm(sc[u], 0u, sel));
        const float a0 = fmaf(qa0, bf_lo(cs[u].x), qb0 * bf_lo(sn[u].x));
        const float a1 = fmaf(qa1, bf_hi(cs[u].x), qb1 * bf_hi(sn[u].x));
        const float a2 = fmaf(qa2, bf_lo(cs[u].y), qb2 * bf_lo(sn[u].y));
        const float a3 = fmaf(qa3, bf_hi(cs[u].y), qb3 * bf_hi(sn[u].y));
        float t = ((float)kv[u].x - z) * a0;
        t = fmaf((float)kv[u].y - z, a1, t);
        t = fmaf((float)kv[u].z - z, a2, t);
        t = fmaf((float)kv[u].w - z, a3, t);
        acc[u] = t * s;
    }
    const bool up = (lane & 16) != 0, up2 = (lane & 8) != 0;
    const float a = (up ? acc[2] : acc[0]) + __shfl_xor_sync(0xffffffffu, up ? acc[0] : acc[2], 16);
    const float b = (up ? acc[3] : acc[1]) + __shfl_xor_sync(0xffffffffu, up ? acc[1] : acc[3], 16);
    float lg = (up2 ? b : a) + __shfl_xor_sync(0xffffffffu, up2 ? a : b, 8);
#pragma unroll
    for (int off = 4; off > 0; off >>= 1) lg += __shfl_xor_sync(0xffffffffu, lg, off);
    asm volatile("{\n.reg .pred p;\nsetp.eq.u32 p, %2, 0;\n@p st.relaxed.gpu.global.u32 [%0], %1;\n}"
                 :: "l"(P.scr->logits + (row + (lane >> 3))), "r"(tagf(lg, tag_of(cnt))), "r"(lane & 7) : "memory");
}

__device__ __forceinline__ float block_sum(float x, float* s_red) {
#pragma unroll
    for (int o = 1; o < 32; o <<= 1) x += __shfl_xor_sync(0xffffffffu, x, o);
    if ((threadIdx.x & 31) == 0) s_red[threadIdx.x >> 5] = x;
    __syncthreads();
    const float4 a = *(const float4*)(s_red), b = *(const float4*)(s_red + 4);
    return ((a.x + a.y) + (a.z + a.w)) + ((b.x + b.y) + (b.z + b.w));
}

__device__ __forceinline__ void s_role(const Params& P, int h, float* sm) {
    constexpr int NB = S / (4 * NT);
    const int t = threadIdx.x;
    const uint32_t tag = tag_of(ld_cnt(P));
#pragma unroll
    for (int i = 0; i < (NC * D + NT - 1) / NT; i++)
        if (t + i * NT < NC * D) st_rlx64(acc_ptr(P, h * NC + (t + i * NT) / D, t % D), tag << 8);
    __threadfence();
    const float* lp = P.scr->logits + (h * S + t * 4);
    uint4 lg[NB];
    for (int it = 0;; it++) {
        uint32_t bad = 0;
#pragma unroll
        for (int j = 0; j < NB; j++) lg[j] = ld_rlx16(lp + j * (4 * NT));
#pragma unroll
        for (int j = 0; j < NB; j++) bad |= bad4(lg[j], tag);
        if (!__any_sync(0xffffffffu, bad & 3u)) break;
        if (it > SPIN_LIMIT) break;
        __nanosleep(500);
    }
    float m = __uint_as_float(lg[0].x);
#pragma unroll
    for (int j = 0; j < NB; j++)
        m = fmaxf(fmaxf(m, fmaxf(__uint_as_float(lg[j].x), __uint_as_float(lg[j].y))),
                  fmaxf(__uint_as_float(lg[j].z), __uint_as_float(lg[j].w)));
#pragma unroll
    for (int o = 1; o < 32; o <<= 1) m = fmaxf(m, __shfl_xor_sync(0xffffffffu, m, o));
    if ((t & 31) == 0) sm[t >> 5] = m;
    __syncthreads();
    {
        const float4 a = *(const float4*)(sm), b = *(const float4*)(sm + 4);
        m = fmaxf(fmaxf(fmaxf(a.x, a.y), fmaxf(a.z, a.w)), fmaxf(fmaxf(b.x, b.y), fmaxf(b.z, b.w)));
    }
    float p[NB][4];
    float l = 0.f;
#pragma unroll
    for (int j = 0; j < NB; j++) {
        p[j][0] = ex2(__uint_as_float(lg[j].x) - m);
        p[j][1] = ex2(__uint_as_float(lg[j].y) - m);
        p[j][2] = ex2(__uint_as_float(lg[j].z) - m);
        p[j][3] = ex2(__uint_as_float(lg[j].w) - m);
        l += (p[j][0] + p[j][1]) + (p[j][2] + p[j][3]);
    }
    float inv;
    asm("rcp.approx.ftz.f32 %0, %1;" : "=f"(inv) : "f"(block_sum(l, sm + NW)));
    const __nv_bfloat16* vsp = P.vs + (h * S + t * 4) * 2;
    const __nv_bfloat16* vzp = P.vz + (h * S + t * 4) * 2;
    float a0 = 0.f, a1 = 0.f;
#pragma unroll
    for (int j0 = 0; j0 < NB; j0 += 4) {
        uint4 sv[4];
#pragma unroll
        for (int k = 0; k < 4; k++) sv[k] = ld_nc16(vsp + (j0 + k) * (8 * NT));
#pragma unroll
        for (int k = 0; k < 4; k++) {
            const uint32_t sc[4] = {sv[k].x, sv[k].y, sv[k].z, sv[k].w};
#pragma unroll
            for (int i = 0; i < 4; i++) {
                a0 = fmaf(p[j0 + k][i], fabsf(bf_lo(sc[i])), a0);
                a1 = fmaf(p[j0 + k][i], fabsf(bf_hi(sc[i])), a1);
            }
        }
    }
    const uint32_t e0 = min(max(__float_as_uint(block_sum(a0 * inv, sm + 2 * NW)) >> 23, 22u), 254u);
    const uint32_t e1 = min(max(__float_as_uint(block_sum(a1 * inv, sm + 3 * NW)) >> 23, 22u), 254u);
    const float i0 = inv * __uint_as_float((274u - e0) << 23), i1 = inv * __uint_as_float((274u - e1) << 23);
    float c0 = 0.f, c1 = 0.f;
    float4* wp = P.scr->wts + (h * (S / 4) + t) * 2;
#pragma unroll 1
    for (int j0 = 0; j0 < NB; j0 += 2) {
        uint4 sv[2], zv[2], gv[2];
#pragma unroll
        for (int k = 0; k < 2; k++) {
            zv[k] = ld_nc16_na(vzp + (j0 + k) * (8 * NT));
            gv[k] = ld_rlx16(lp + (j0 + k) * (4 * NT));
            sv[k] = ld_nc16(vsp + (j0 + k) * (8 * NT));
        }
#pragma unroll
        for (int k = 0; k < 2; k++) {
            const int j = j0 + k;
            const uint32_t sc[4] = {sv[k].x, sv[k].y, sv[k].z, sv[k].w};
            const uint32_t zz[4] = {zv[k].x, zv[k].y, zv[k].z, zv[k].w};
            const uint32_t gg[4] = {gv[k].x, gv[k].y, gv[k].z, gv[k].w};
            uint32_t w0[4], w1[4];
#pragma unroll
            for (int i = 0; i < 4; i++) {
                const float pp = ex2(__uint_as_float(gg[i]) - m);
                w0[i] = tagf(pp * i0 * bf_lo(sc[i]), tag);
                w1[i] = tagf(pp * i1 * bf_hi(sc[i]), tag);
                c0 = fmaf(__uint_as_float(w0[i]), bf_lo(zz[i]), c0);
                c1 = fmaf(__uint_as_float(w1[i]), bf_hi(zz[i]), c1);
            }
            st_rlx16(wp + j * (2 * NT), w0[0], w0[1], w0[2], w0[3]);
            st_rlx16(wp + j * (2 * NT) + 1, w1[0], w1[1], w1[2], w1[3]);
        }
    }
    c0 = block_sum(c0, sm + 4 * NW);
    c1 = block_sum(c1, sm + 5 * NW);
    if (t == 0) {
        st_rlx8(P.scr->corr + h * 2, tagf(c0, tag), ((e0 - 20u) << 23) | tag);
        st_rlx8(P.scr->corr + h * 2 + 1, tagf(c1, tag), ((e1 - 20u) << 23) | tag);
    }
}

__device__ __forceinline__ void v_role(const Params& P, uint32_t off, const int4 (&vv)[U], float* sm) {
    const int t = threadIdx.x, w = t >> 5, lane = t & 31;
    const uint32_t h = off >> 22, j = blockIdx.x;
    const char* wp = BYTES(P.scr->wts, (off >> 11) * 32 + (lane & 16));
    uint4 wt = ld_rlx16(wp);
    const uint32_t tag = tag_of(ld_cnt(P));
    for (int it = 0; bad4(wt, tag) & 3u; it++) {
        if (it > SPIN_LIMIT) break;
        __nanosleep(100);
        wt = ld_rlx16(wp);
    }
    const float wu[4] = {__uint_as_float(wt.x), __uint_as_float(wt.y), __uint_as_float(wt.z), __uint_as_float(wt.w)};
    float o0 = (float)vv[0].x * wu[0], o1 = (float)vv[0].y * wu[0], o2 = (float)vv[0].z * wu[0], o3 = (float)vv[0].w * wu[0];
#pragma unroll
    for (int u = 1; u < U; u++) {
        o0 = fmaf((float)vv[u].x, wu[u], o0);
        o1 = fmaf((float)vv[u].y, wu[u], o1);
        o2 = fmaf((float)vv[u].z, wu[u], o2);
        o3 = fmaf((float)vv[u].w, wu[u], o3);
    }
    *(float4*)(sm + w * D + lane * 4) = make_float4(o0, o1, o2, o3);
    __syncthreads();
    if (t < D) {
        float r[NW];
#pragma unroll
        for (int k = 0; k < NW; k++) r[k] = sm[k * D + t];
        const float o = ((r[0] + r[1]) + (r[2] + r[3])) + ((r[4] + r[5]) + (r[6] + r[7]));
        const unsigned long long a = ((unsigned long long)__float2ll_rn(o) << CB) + 1ull;
        asm volatile("red.relaxed.gpu.global.add.L2::cache_hint.u64 [%0], %1, %2;"
                     :: "l"(acc_ptr(P, h * NC + j % NC, t)), "l"(a), "l"(pol_first()) : "memory");
    }
}

constexpr int PSTR = 20;
__device__ __forceinline__ int ld_half32(const int* p) {
    int v;
    asm volatile("ld.global.nc.L1::no_allocate.L2::128B.s32 %0, [%1];" : "=r"(v) : "l"(p));
    return v;
}
__device__ __forceinline__ float4 lds16(uint32_t a) {
    float4 v;
    asm volatile("ld.volatile.shared.v4.f32 {%0,%1,%2,%3}, [%4];" : "=f"(v.x), "=f"(v.y), "=f"(v.z), "=f"(v.w) : "r"(a) : "memory");
    return v;
}
__device__ __forceinline__ float acc_val(const uint2& a) {
    return fmaf((float)(int)a.y, (float)(1 << (32 - CB)), (float)(int)(a.x >> CB));
}
__device__ __forceinline__ void f_role(const Params& P, uint32_t f, float* sm) {
    const int t = threadIdx.x, w = t >> 5, lane = t & 31;
    const uint32_t h = f / (D / FC), c = f % (D / FC), g = c * FC / 64;
    uint32_t sb = (uint32_t)__cvta_generic_to_shared(sm) + ((lane % FC) * PSTR + w * 2 + lane / FC) * 4;
    PIN32(sb);
    if (w == NW - 1) {
        const float2* cp = P.scr->corr + (h * 2 + g);
        const unsigned long long* ap = acc_ptr(P, h * NC, c * FC + lane % FC);
        uint2 a0 = ld_rlx8(ap), a1 = ld_rlx8(ap + (D / 16) * AS);
        uint2 cu = ld_rlx8(cp);
        const uint32_t tag = tag_of(ld_cnt(P));
        const uint32_t want0 = tag << 8 | EARLY / NC, want1 = tag << 8 | (EARLY + 1) / NC;
        uint32_t sa = (sb & ~7u) - (NW - 1) * 8;
        __nv_bfloat16* op = P.out + (h * D + c * FC + lane);
        unsigned* cn = P.scr->cnt + lane;
        uint32_t one = 1;
        PIN32(sa); PIN64(op); PIN64(cn); PIN32(one);
        for (int it = 0; ((cu.x ^ tag) | (cu.y ^ tag)) & 3u; it++) {
            if (it > SPIN_LIMIT) break;
            cu = ld_rlx8(cp);
        }
        for (int it = 0;; it++) {
            if ((((a0.x ^ want0) | (a1.x ^ want1)) & ((1u << CB) - 1u)) == 0 || it > SPIN_LIMIT) break;
            a0 = ld_rlx8(ap);
            a1 = ld_rlx8(ap + (D / 16) * AS);
        }
        float own = (acc_val(a0) - __uint_as_float(cu.x)) + acc_val(a1);
        float scale = __uint_as_float(cu.y & ~3u);
        asm volatile("bar.sync 1, 256;" : "+f"(own), "+f"(scale) :: "memory");
        const float4 p0 = lds16(sa), p1 = lds16(sa + 16), p2 = lds16(sa + 32);
        float2 p3;
        asm volatile("ld.volatile.shared.v2.f32 {%0,%1}, [%2];" : "=f"(p3.x), "=f"(p3.y) : "r"(sa + 48) : "memory");
        const float xa = (((p0.x + p0.y) + (p0.z + p0.w)) + own) + ((p1.x + p1.y) + (p1.z + p1.w));
        const float x = fmaf(((p2.x + p2.y) + (p2.z + p2.w)) + (p3.x + p3.y), scale, xa * scale);
        asm volatile("{\n.reg .pred p;\n.reg .b32 r;\nsetp.lt.u32 p, %3, %4;\ncvt.rn.bf16x2.f32 r, %1, %1;\n@p st.global.u16 [%0], r;\nred.relaxed.gpu.global.add.u32 [%2], %5;\n}"
                     :: "l"(op), "f"(x), "l"(cn), "r"(lane), "n"(FC), "r"(one) : "memory");
        return;
    }
    constexpr int RL = 16;
    __syncwarp();
    const uint32_t row = h * S + f_block(h) * (NW * U) + w * 32 + (lane & 16);
    const int* src = (const int*)P.qv + (row * D + c * FC + lane % FC);
    const float4* wp = P.scr->wts + (row / 2 + g);
    uint4 wt[RL / 4];
    int vv[RL];
    const int* src2 = P.qv2 + (row * D + c * FC + lane % FC);
#pragma unroll
    for (int u = 0; u < RL; u++) vv[u] = ld_half32((u < RL - 1 ? src : src2) + u * D);
#pragma unroll
    for (int k = 0; k < RL / 4; k++) wt[k] = ld_rlx16(wp + k * 2);
    uint32_t tag = ld_cnt(P) / NF + 1u;
    PIN32(tag);
    float o[4];
#define WT(i_) __uint_as_float((i_) % 4 == 0 ? wt[(i_) / 4].x : (i_) % 4 == 1 ? wt[(i_) / 4].y : (i_) % 4 == 2 ? wt[(i_) / 4].z : wt[(i_) / 4].w)
    auto bad16 = [&]() {
        uint32_t b[8];
#pragma unroll
        for (int k = 0; k < 4; k++) {
            b[2 * k] = (wt[k].x ^ tag) | (wt[k].y ^ tag); b[2 * k + 1] = (wt[k].z ^ tag) | (wt[k].w ^ tag);
            asm("" : "+r"(b[2 * k]), "+r"(b[2 * k + 1]));
        }
        uint32_t x = b[0] | b[1] | b[2], y = b[3] | b[4] | b[5];
        asm("" : "+r"(x), "+r"(y));
        y = y | b[6] | b[7];
        asm("" : "+r"(y));
        return (x | y) & 3u;
    };
    auto dot = [&](float z) {
        o[0] = o[1] = o[2] = o[3] = z;
#pragma unroll
        for (int i = 0; i < RL - 4; i++) o[i % 4] = fmaf((float)vv[i], WT(i), o[i % 4]);
        o[0] += o[2]; o[1] += o[3];
#pragma unroll
        for (int i = RL - 4; i < RL; i++) o[i % 2] = fmaf((float)vv[i], WT(i), o[i % 2]);
        return o[0] + o[1];
    };
    const uint32_t bb = bad16();
    const bool bad = __any_sync(0xffffffffu, bb);
    asm volatile("{\n.reg .pred p;\nsetp.eq.u32 p, %2, 0;\nst.volatile.shared.f32 [%0], %1;\n@p bar.arrive 1, 256;\n@p exit;\n}"
                 :: "r"(sb), "f"(dot(__uint_as_float(bb))), "r"((uint32_t)bad) : "memory");
    for (int it = 0; it < SPIN_LIMIT; it++) {
        __nanosleep(100);
#pragma unroll
        for (int k = 0; k < RL / 4; k++) wt[k] = ld_rlx16(wp + k * 2);
        if (!__any_sync(0xffffffffu, bad16())) break;
    }
    asm volatile("st.volatile.shared.f32 [%0], %1;\nbar.arrive 1, 256;" :: "r"(sb), "f"(dot(0.f)) : "memory");
}

__global__ void __cluster_dims__(CL, 1, 1) __launch_bounds__(NT, 4) attn_kernel(const __grid_constant__ Params P) {
    __shared__ __align__(16) float sm[NW * D];
    const uint32_t x = blockIdx.x, y = blockIdx.y, t = threadIdx.x;
    const uint32_t a = t * 16 + (t >> 5) * 1536;
    const uint32_t ko = a + (x << 13) + ((y + (y & ~1u)) << 21) + (t >> 7) * ((1u << 22) - (1u << 13));
    const uint32_t vo = a + (x << 14) + ((y - H) << 22);
    uint32_t off = y < H ? ko : vo;
    const ulonglong2* tab = (const ulonglong2*)&P + y / H;
    const ulonglong2 t0 = tab[0];
    const ulonglong2 t2 = tab[2], t3 = tab[3], t4 = tab[4], t5 = tab[5];
    const char* src = BYTES(t0.x, off);
    PIN64(src); PIN32(off);
    const bool other = x >= SEG || y >= 2 * H || x - f_block(y - H) < SEG - EARLY;
    int4 d[U];
    asm volatile("{\n.reg .pred p;\n.reg .b64 q;\nsetp.eq.u32 p, %17, 0;\ncreatepolicy.fractional.L2::evict_first.b64 q, 1.0;\n"
                 "@p ld.global.nc.L1::no_allocate.L2::cache_hint.v4.s32 {%0,%1,%2,%3}, [%16], q;\n"
                 "@p ld.global.nc.L1::no_allocate.L2::cache_hint.v4.s32 {%4,%5,%6,%7}, [%16+512], q;\n"
                 "@p ld.global.nc.L1::no_allocate.L2::cache_hint.v4.s32 {%8,%9,%10,%11}, [%16+1024], q;\n"
                 "@p ld.global.nc.L1::no_allocate.L2::cache_hint.v4.s32 {%12,%13,%14,%15}, [%16+1536], q;\n}"
                 : "=r"(d[0].x), "=r"(d[0].y), "=r"(d[0].z), "=r"(d[0].w), "=r"(d[1].x), "=r"(d[1].y), "=r"(d[1].z), "=r"(d[1].w),
                   "=r"(d[2].x), "=r"(d[2].y), "=r"(d[2].z), "=r"(d[2].w), "=r"(d[3].x), "=r"(d[3].y), "=r"(d[3].z), "=r"(d[3].w)
                 : "l"(src), "r"((uint32_t)other));
    if (other) {
        if (x >= SEG) {
            const int h = (int)y - (HP + SD);
            if (x == SEG + 1 && y + PD < H && threadIdx.x < 2 * HP) {
                const uint32_t yy = y + PD, i = threadIdx.x;
                const __nv_bfloat16* a = (i >= HP ? P.ks : P.kz) + (((yy & ~(HP - 1u)) + i % HP) * S + yy % HP * (S / HP)) * 2;
                asm volatile("cp.async.bulk.prefetch.L2.global [%0], %1;" :: "l"(a), "r"(S / HP * 4) : "memory");
            }
            if (x == SEG && h >= 0 && h < H) s_role(P, h, sm);
        } else if (y >= 2 * H) {
            f_role(P, x, sm);
        }
        return;
    }
    KAddr A;
    {
        const uint32_t l8 = (t & 31) * 8, qo = (off >> 22) * (D * 2) + l8, co = (off >> 1) & (S * D * 2 - 1);
        A.qa = BYTES(t2.x, qo); A.qb = BYTES(t2.x, qo ^ 128u); A.qc = BYTES(t2.y, l8); A.qs = BYTES(t3.x, l8);
        A.cp = BYTES(t3.y, co); A.sp = BYTES(t4.x, co ^ 128u);
        A.ks = BYTES(t4.y, (off >> 9) * 4); A.kz = BYTES(t5.x, (off >> 9) * 4);
        A.scr = (char*)t0.y;
    }
    asm volatile("" : "+l"(A.qa), "+l"(A.qb), "+l"(A.qc), "+l"(A.qs));
    asm volatile("" : "+l"(A.cp), "+l"(A.sp), "+l"(A.ks), "+l"(A.kz));
    if (y >= H - HP) {
        if (y >= H) v_role(P, off, d, sm);
        else k_role<true>(P, off, d, A);
        return;
    }
    k_role<false>(P, off, d, A);
}

}

extern "C" void kernel_launch(void* const* d_in, const int* in_sizes, int n_in, void* d_out, int out_size) {
    (void)in_sizes; (void)n_in; (void)out_size;
    Params P;
    P.q = (const __nv_bfloat16*)d_in[0];
    P.qk = (const int4*)d_in[1];
    P.ks = (const __nv_bfloat16*)d_in[2];
    P.kz = (const __nv_bfloat16*)d_in[3];
    P.qv = (const int4*)d_in[4];
    P.vs = (const __nv_bfloat16*)d_in[5];
    P.vz = (const __nv_bfloat16*)d_in[6];
    P.qcos = (const __nv_bfloat16*)d_in[7];
    P.qsin = (const __nv_bfloat16*)d_in[8];
    P.kcos = (const __nv_bfloat16*)d_in[9];
    P.ksin = (const __nv_bfloat16*)d_in[10];
    P.out = (__nv_bfloat16*)d_out;
    void* scr = nullptr;
    cudaGetSymbolAddress(&scr, g_scr);
    P.scr = P.scr2 = (Scratch*)scr;
    P.pad = nullptr;
    P.qv2 = (const int*)d_in[4];
    attn_kernel<<<dim3(GX, GY), NT>>>(P);
}
```
